```python
import torch

def _softmax(x, axis=-1):
    return torch.softmax(x, dim=axis)
def _gelu(x):
    return torch.nn.functional.gelu(x, approximate="tanh")
def _silu(x):
    return torch.nn.functional.silu(x)
def _sigmoid(x):
    return torch.sigmoid(x)
def _layernorm(x, axis=-1, eps=1e-5):
    m = x.mean(dim=axis, keepdim=True)
    v = x.var(dim=axis, keepdim=True, unbiased=False)
    return (x - m) / torch.sqrt(v + eps)
def _scatter_add(tgt, idx, src, axis=0):
    return tgt.clone().index_add_(axis, idx, src)
def _segment_sum(src, seg, n):
    out = torch.zeros((n,) + src.shape[1:], dtype=src.dtype)
    return out.index_add_(0, seg, src)
def _pad(x, pw):
    flat = tuple(v for pair in reversed(pw) for v in pair)
    return torch.nn.functional.pad(x, flat)

kernel_name = 'standalone__gqa_softmax__near_ridge'

def setup_inputs():

    _w = (lambda a: (lambda t: t.to(torch.bfloat16) if t.is_floating_point() else t)(torch.as_tensor(a)))
    B, Hq, Hkv, Sq, Sk, D = 16, 16, 8, 192, 512, 256
    return {
        "q": _w((lambda *s: torch.randn(*s, dtype=torch.bfloat16) * 0.8)(B, Hq, Sq, D)),
        "k": _w((lambda *s: torch.randn(*s, dtype=torch.bfloat16) * 0.8)(B, Hkv, Sk, D)),
        "v": _w((lambda *s: torch.randn(*s, dtype=torch.bfloat16) * 0.05)(B, Hkv, Sk, D)),
    }

def reference(q, k, v):
    B, Hq, Sq, D = q.shape
    Hkv = k.shape[1]
    rep = Hq // Hkv
    k = (lambda x, n, axis: torch.repeat_interleave(x, n, dim=axis))(k, rep, axis=1)
    v = (lambda x, n, axis: torch.repeat_interleave(x, n, dim=axis))(v, rep, axis=1)
    scale = D ** -0.5
    scores = torch.einsum("bhqd,bhkd->bhqk", q, k) * scale
    p = _softmax(scores, axis=-1)
    return torch.einsum("bhqk,bhkd->bhqd", p, v)
```

```cpp
#include <cuda_runtime.h>
#include <cuda_bf16.h>
#include <cuda.h>
#include <stdint.h>

#define GRID 132
#define WFENCE 0
#define EPSP 1

#define TUNABLES(X)                                                                       \
    X(parity, 1) X(odd_delay, 4000) X(start_delay, 0) X(stgap, 250) X(hint_q, 1)          \
    X(hint_kv, 1) X(kv_frac, 100) X(qpf1, 8) X(qpf2, 26) X(qpfc1, 12) X(qpfc2, 12)        \
    X(qpfl, 32) X(o0pos, 1) X(o1pos, 2) X(nostore, 0) X(samekv, 0) X(hint_o, 0) X(x0, 0) X(x1, 0) X(x2, 0)
struct Tune {
#define X(n, v) static constexpr int n = v;
    TUNABLES(X)
#undef X
};
#define TD(n) (Tune::n)
#define TH(n) (Tune::n)

namespace {

constexpr int kPairs = 128;
constexpr int kRowsPerPair = 384;
constexpr int kKeys = 512;
constexpr int kTriples = GRID / 3;
constexpr int kSlots = 7;
constexpr int kSlotBytes = 32768;
constexpr int kSmemBytes = kSlots * kSlotBytes + 256;
constexpr int kMaxLoads = 56;
constexpr int kMaxSteps = 26;

struct Sched {
    uint32_t prod[2][kMaxLoads];
    uint32_t cons[2][kMaxSteps];
    uint32_t nloads[2];
};

__device__ __forceinline__ void mbar_init(uint32_t bar, uint32_t cnt) {
    asm volatile("mbarrier.init.shared::cta.b64 [%0], %1;" ::"r"(bar), "r"(cnt) : "memory");
}
__device__ __forceinline__ void mbar_expect_tx(uint32_t bar, uint32_t bytes) {
    asm volatile("mbarrier.arrive.expect_tx.shared::cta.b64 _, [%0], %1;" ::"r"(bar), "r"(bytes) : "memory");
}
__device__ __forceinline__ void mbar_arrive(uint32_t bar) {
    asm volatile("mbarrier.arrive.shared::cta.b64 _, [%0];" ::"r"(bar) : "memory");
}
__device__ __forceinline__ void mbar_arrive_n(uint32_t bar, uint32_t n) {
    asm volatile("mbarrier.arrive.shared::cta.b64 _, [%0], %1;" ::"r"(bar), "r"(n) : "memory");
}
__device__ __forceinline__ void mbar_arrive_if(bool pred, uint32_t bar) {
    asm volatile("{ .reg .pred p; setp.ne.u32 p, %1, 0; @p mbarrier.arrive.shared::cta.b64 _, [%0]; }" ::"r"(bar), "r"((uint32_t)pred) : "memory");
}
__device__ __forceinline__ void mbar_arrive2_if(bool pred, uint32_t bar) {
    asm volatile("{ .reg .pred p; setp.ne.u32 p, %1, 0; @p mbarrier.arrive.shared::cta.b64 _, [%0], 2; }" ::"r"(bar), "r"((uint32_t)pred) : "memory");
}
__device__ __forceinline__ void mbar_wait(uint32_t bar, uint32_t parity) {
    asm volatile(
        "{\n"
        ".reg .pred p, q;\n"
        ".reg .u32 n;\n"
        "mbarrier.try_wait.parity.shared::cta.b64 p, [%0], %1;\n"
        "@p bra DONE;\n"
        "mov.u32 n, 0;\n"
        "LOOP:\n"
        "mbarrier.try_wait.parity.shared::cta.b64 p, [%0], %1;\n"
        "@p bra DONE;\n"
        "add.u32 n, n, 1;\n"
        "setp.lt.u32 q, n, 4194304;\n"
        "@q bra LOOP;\n"
        "trap;\n"
        "DONE:\n"
        "}\n" ::"r"(bar), "r"(parity) : "memory");
}
__device__ __forceinline__ void tma_load(uint32_t dst, const CUtensorMap* m, int row, uint32_t bar) {
    asm volatile(
        "cp.async.bulk.tensor.3d.shared::cluster.global.mbarrier::complete_tx::bytes [%0], [%1, {%3, %4, %3}], [%2];"
        ::"r"(dst), "l"(m), "r"(bar), "r"(0), "r"(row) : "memory");
}
__device__ __forceinline__ void tma_load_hint(uint32_t dst, const CUtensorMap* m, int row, uint32_t bar, uint64_t pol) {
    asm volatile(
        "cp.async.bulk.tensor.3d.shared::cluster.global.mbarrier::complete_tx::bytes.L2::cache_hint [%0], [%1, {%3, %4, %3}], [%2], %5;"
        ::"r"(dst), "l"(m), "r"(bar), "r"(0), "r"(row), "l"(pol) : "memory");
}
__device__ __forceinline__ void tma_store(const CUtensorMap* m, uint32_t src, int row, int chunk) {
    asm volatile("cp.async.bulk.tensor.3d.global.shared::cta.bulk_group [%0, {%2, %3, %4}], [%1];"
                 ::"l"(m), "r"(src), "r"(0), "r"(row), "r"(chunk) : "memory");
}
__device__ __forceinline__ uint32_t clock32() {
    uint32_t t;
    asm volatile("mov.u32 %0, %%clock;" : "=r"(t));
    return t;
}
__device__ __forceinline__ void wg_fence() { asm volatile("wgmma.fence.sync.aligned;" ::: "memory"); }
__device__ __forceinline__ void wg_commit() { asm volatile("wgmma.commit_group.sync.aligned;" ::: "memory"); }
template <int N>
__device__ __forceinline__ void wg_wait() { asm volatile("wgmma.wait_group.sync.aligned %0;" ::"n"(N) : "memory"); }
template <int n>
__device__ __forceinline__ void fence_regs(float (&r)[n]) {
#pragma unroll
    for (int i = 0; i < n; i++) asm volatile("" : "+f"(r[i])::"memory");
}
template <int n>
__device__ __forceinline__ void fence_regs(uint32_t (&r)[n]) {
#pragma unroll
    for (int i = 0; i < n; i++) asm volatile("" : "+r"(r[i])::"memory");
}
__device__ __forceinline__ void bar_sync(int id, int n) { asm volatile("bar.sync %0, %1;" ::"r"(id), "r"(n) : "memory"); }
__device__ __forceinline__ void bar_arrive(int id, int n) { asm volatile("bar.arrive %0, %1;" ::"r"(id), "r"(n) : "memory"); }
__device__ __forceinline__ float ex2(float x) {
    float y;
    asm("ex2.approx.ftz.f32 %0, %1;" : "=f"(y) : "f"(x));
    return y;
}
__device__ __forceinline__ uint32_t pack_bf16(float lo, float hi) {
    uint32_t r;
    asm("cvt.rn.bf16x2.f32 %0, %1, %2;" : "=r"(r) : "f"(hi), "f"(lo));
    return r;
}
__device__ __forceinline__ uint64_t mk_desc(uint32_t lo) { return ((uint64_t)(0x40000000u | 64u) << 32) | lo; }

template <int SCALE_D>
__device__ __forceinline__ void wgmma_ss_n64(float (&d)[32], uint64_t da, uint64_t db) {
    asm volatile("{ .reg .pred p; setp.ne.b32 p, %34, 0;\n"
        "wgmma.mma_async.sync.aligned.m64n64k16.f32.bf16.bf16 "
        "{%0, %1, %2, %3, %4, %5, %6, %7, %8, %9, %10, %11, %12, %13, %14, %15, %16, %17, %18, %19, %20, %21, %22, %23, %24, %25, %26, %27, %28, %29, %30, %31}, "
        "%32, %33, p, 1, 1, 0, 0; }\n"
        : "+f"(d[0]), "+f"(d[1]), "+f"(d[2]), "+f"(d[3]), "+f"(d[4]), "+f"(d[5]), "+f"(d[6]), "+f"(d[7]), "+f"(d[8]), "+f"(d[9]), "+f"(d[10]), "+f"(d[11]), "+f"(d[12]), "+f"(d[13]), "+f"(d[14]), "+f"(d[15]), "+f"(d[16]), "+f"(d[17]), "+f"(d[18]), "+f"(d[19]), "+f"(d[20]), "+f"(d[21]), "+f"(d[22]), "+f"(d[23]), "+f"(d[24]), "+f"(d[25]), "+f"(d[26]), "+f"(d[27]), "+f"(d[28]), "+f"(d[29]), "+f"(d[30]), "+f"(d[31])
        : "l"(da), "l"(db), "n"(SCALE_D));
}

__device__ __forceinline__ void wgmma_rs_n256_tb(float (&d)[128], uint32_t a0, uint32_t a1, uint32_t a2, uint32_t a3, uint64_t db, int scale_d) {
    asm volatile("{ .reg .pred p; setp.ne.b32 p, %133, 0;\n"
        "wgmma.mma_async.sync.aligned.m64n256k16.f32.bf16.bf16 "
        "{%0, %1, %2, %3, %4, %5, %6, %7, %8, %9, %10, %11, %12, %13, %14, %15, "
        "%16, %17, %18, %19, %20, %21, %22, %23, %24, %25, %26, %27, %28, %29, %30, %31, "
        "%32, %33, %34, %35, %36, %37, %38, %39, %40, %41, %42, %43, %44, %45, %46, %47, "
        "%48, %49, %50, %51, %52, %53, %54, %55, %56, %57, %58, %59, %60, %61, %62, %63, "
        "%64, %65, %66, %67, %68, %69, %70, %71, %72, %73, %74, %75, %76, %77, %78, %79, "
        "%80, %81, %82, %83, %84, %85, %86, %87, %88, %89, %90, %91, %92, %93, %94, %95, "
        "%96, %97, %98, %99, %100, %101, %102, %103, %104, %105, %106, %107, %108, %109, %110, %111, "
        "%112, %113, %114, %115, %116, %117, %118, %119, %120, %121, %122, %123, %124, %125, %126, %127}, "
        "{%128, %129, %130, %131}, %132, p, 1, 1, 1; }\n"
        : "+f"(d[0]), "+f"(d[1]), "+f"(d[2]), "+f"(d[3]), "+f"(d[4]), "+f"(d[5]), "+f"(d[6]), "+f"(d[7]),
          "+f"(d[8]), "+f"(d[9]), "+f"(d[10]), "+f"(d[11]), "+f"(d[12]), "+f"(d[13]), "+f"(d[14]), "+f"(d[15]),
          "+f"(d[16]), "+f"(d[17]), "+f"(d[18]), "+f"(d[19]), "+f"(d[20]), "+f"(d[21]), "+f"(d[22]), "+f"(d[23]),
          "+f"(d[24]), "+f"(d[25]), "+f"(d[26]), "+f"(d[27]), "+f"(d[28]), "+f"(d[29]), "+f"(d[30]), "+f"(d[31]),
          "+f"(d[32]), "+f"(d[33]), "+f"(d[34]), "+f"(d[35]), "+f"(d[36]), "+f"(d[37]), "+f"(d[38]), "+f"(d[39]),
          "+f"(d[40]), "+f"(d[41]), "+f"(d[42]), "+f"(d[43]), "+f"(d[44]), "+f"(d[45]), "+f"(d[46]), "+f"(d[47]),
          "+f"(d[48]), "+f"(d[49]), "+f"(d[50]), "+f"(d[51]), "+f"(d[52]), "+f"(d[53]), "+f"(d[54]), "+f"(d[55]),
          "+f"(d[56]), "+f"(d[57]), "+f"(d[58]), "+f"(d[59]), "+f"(d[60]), "+f"(d[61]), "+f"(d[62]), "+f"(d[63]),
          "+f"(d[64]), "+f"(d[65]), "+f"(d[66]), "+f"(d[67]), "+f"(d[68]), "+f"(d[69]), "+f"(d[70]), "+f"(d[71]),
          "+f"(d[72]), "+f"(d[73]), "+f"(d[74]), "+f"(d[75]), "+f"(d[76]), "+f"(d[77]), "+f"(d[78]), "+f"(d[79]),
          "+f"(d[80]), "+f"(d[81]), "+f"(d[82]), "+f"(d[83]), "+f"(d[84]), "+f"(d[85]), "+f"(d[86]), "+f"(d[87]),
          "+f"(d[88]), "+f"(d[89]), "+f"(d[90]), "+f"(d[91]), "+f"(d[92]), "+f"(d[93]), "+f"(d[94]), "+f"(d[95]),
          "+f"(d[96]), "+f"(d[97]), "+f"(d[98]), "+f"(d[99]), "+f"(d[100]), "+f"(d[101]), "+f"(d[102]), "+f"(d[103]),
          "+f"(d[104]), "+f"(d[105]), "+f"(d[106]), "+f"(d[107]), "+f"(d[108]), "+f"(d[109]), "+f"(d[110]), "+f"(d[111]),
          "+f"(d[112]), "+f"(d[113]), "+f"(d[114]), "+f"(d[115]), "+f"(d[116]), "+f"(d[117]), "+f"(d[118]), "+f"(d[119]),
          "+f"(d[120]), "+f"(d[121]), "+f"(d[122]), "+f"(d[123]), "+f"(d[124]), "+f"(d[125]), "+f"(d[126]), "+f"(d[127])
        : "r"(a0), "r"(a1), "r"(a2), "r"(a3), "l"(db), "r"(scale_d));
}

#define TR(g, i)

__device__ __forceinline__ void issue_qk(float (&s)[32], uint32_t q_lo, uint32_t k_lo) {
    wgmma_ss_n64<0>(s, mk_desc(q_lo), mk_desc(k_lo));
#pragma unroll
    for (int k = 1; k < 16; k++) {
        const uint32_t off = ((k >> 2) * 8192 + (k & 3) * 32) >> 4;
        wgmma_ss_n64<1>(s, mk_desc(q_lo + off), mk_desc(k_lo + off));
    }
    wg_commit();
}
__device__ __forceinline__ void issue_pv(float (&o)[128], uint32_t (&p)[16], uint32_t v_lo, int accumulate) {
#pragma unroll
    for (int k = 0; k < 4; k++)
        wgmma_rs_n256_tb(o, p[4 * k], p[4 * k + 1], p[4 * k + 2], p[4 * k + 3], mk_desc(v_lo + k * 128), k ? 1 : accumulate);
    wg_commit();
}

constexpr float kScaleLog2 = 0.0625f * 1.4426950408889634f;

__device__ __forceinline__ void sched_point() { asm volatile("pmevent 0;" ::: "memory"); }

__device__ __forceinline__ void exp_and_sum(float (&s)[32], float& r0, float& r1) {
#pragma unroll
    for (int i = 0; i < 10; i++) {
        if (i < 8) {
#pragma unroll
            for (int k = 0; k < 4; k++) {
                s[4 * i + k] = ex2(s[4 * i + k]);
                asm volatile("" : "+f"(s[4 * i + k])::"memory");
            }
        }
        if (i > 1) {
            r0 += s[4 * i - 8];
            r1 += s[4 * i - 6];
            r0 += s[4 * i - 7];
            r1 += s[4 * i - 5];
            asm volatile("" : "+f"(r0), "+f"(r1)::"memory");
        }
        if (i > 0 && i < 8) sched_point();
    }
}
__device__ __forceinline__ void row_max(const float (&s)[32], float& x0, float& x1) {
    x0 = fmaxf(s[0], s[1]);
    x1 = fmaxf(s[2], s[3]);
    float y0 = fmaxf(s[4], s[5]), y1 = fmaxf(s[6], s[7]);
#pragma unroll
    for (int i = 2; i < 8; i += 2) {
        x0 = fmaxf(x0, fmaxf(s[4 * i], s[4 * i + 1]));
        x1 = fmaxf(x1, fmaxf(s[4 * i + 2], s[4 * i + 3]));
        y0 = fmaxf(y0, fmaxf(s[4 * i + 4], s[4 * i + 5]));
        y1 = fmaxf(y1, fmaxf(s[4 * i + 6], s[4 * i + 7]));
    }
    x0 = fmaxf(x0, y0);
    x1 = fmaxf(x1, y1);
    x0 = fmaxf(x0, __shfl_xor_sync(0xffffffffu, x0, 1));
    x1 = fmaxf(x1, __shfl_xor_sync(0xffffffffu, x1, 1));
    x0 = fmaxf(x0, __shfl_xor_sync(0xffffffffu, x0, 2));
    x1 = fmaxf(x1, __shfl_xor_sync(0xffffffffu, x1, 2));
}
__device__ __forceinline__ void softmax_first(float (&s)[32], float& c0, float& c1, float& l0, float& l1) {
    float x0, x1;
    row_max(s, x0, x1);
    c0 = -x0 * kScaleLog2;
    c1 = -x1 * kScaleLog2;
#pragma unroll
    for (int i = 0; i < 8; i++) {
        s[4 * i] = fmaf(s[4 * i], kScaleLog2, c0);
        s[4 * i + 1] = fmaf(s[4 * i + 1], kScaleLog2, c0);
        s[4 * i + 2] = fmaf(s[4 * i + 2], kScaleLog2, c1);
        s[4 * i + 3] = fmaf(s[4 * i + 3], kScaleLog2, c1);
        if (i % 2 == 1) { fence_regs(s); sched_point(); }
    }
    l0 = 0.f;
    l1 = 0.f;
    exp_and_sum(s, l0, l1);
}
#define SLACK 8.0f
constexpr float kSlack = SLACK;
__device__ __forceinline__ bool softmax_next(float (&s)[32], float& c0, float& c1, float& l0, float& l1, float& a0, float& a1) {
    int mx = 0, my = 0;
#pragma unroll
    for (int i = 0; i < 8; i++) {
        s[4 * i] = fmaf(s[4 * i], kScaleLog2, c0);
        s[4 * i + 1] = fmaf(s[4 * i + 1], kScaleLog2, c0);
        s[4 * i + 2] = fmaf(s[4 * i + 2], kScaleLog2, c1);
        s[4 * i + 3] = fmaf(s[4 * i + 3], kScaleLog2, c1);
        mx = __vimax3_s32(mx, __float_as_int(s[4 * i]), __float_as_int(s[4 * i + 1]));
        my = __vimax3_s32(my, __float_as_int(s[4 * i + 2]), __float_as_int(s[4 * i + 3]));
    }
    const bool rescale = __any_sync(0xffffffffu, max(mx, my) > __float_as_int(kSlack));
    if (rescale) {
        float x0, x1;
        row_max(s, x0, x1);
        x0 = fmaxf(x0, 0.f);
        x1 = fmaxf(x1, 0.f);
        a0 = ex2(-x0);
        a1 = ex2(-x1);
        c0 -= x0;
        c1 -= x1;
        l0 *= a0;
        l1 *= a1;
#pragma unroll
        for (int i = 0; i < 8; i++) {
            s[4 * i] -= x0;
            s[4 * i + 1] -= x0;
            s[4 * i + 2] -= x1;
            s[4 * i + 3] -= x1;
        }
    }
    exp_and_sum(s, l0, l1);
    return rescale;
}
__device__ __forceinline__ void pack_p(const float (&s)[32], uint32_t (&p)[16]) {
#pragma unroll
    for (int i = 0; i < 16; i++) p[i] = pack_bf16(s[2 * i], s[2 * i + 1]);
}
__device__ __forceinline__ void inv_row_sum(float l0, float l1, float& i0, float& i1) {
    l0 += __shfl_xor_sync(0xffffffffu, l0, 1);
    l1 += __shfl_xor_sync(0xffffffffu, l1, 1);
    l0 += __shfl_xor_sync(0xffffffffu, l0, 2);
    l1 += __shfl_xor_sync(0xffffffffu, l1, 2);
    asm("rcp.approx.ftz.f32 %0, %1;" : "=f"(i0) : "f"(l0));
    asm("rcp.approx.ftz.f32 %0, %1;" : "=f"(i1) : "f"(l1));
}
template <int OFF>
__device__ __forceinline__ void stsm_x4(uint32_t addr, float r0, float r1, float r2, float r3) {
    asm volatile("stmatrix.sync.aligned.m8n8.x4.shared.b16 [%0 + %5], {%1, %2, %3, %4};"
                 ::"r"(addr), "r"(__float_as_uint(r0)), "r"(__float_as_uint(r1)), "r"(__float_as_uint(r2)),
                   "r"(__float_as_uint(r3)), "n"(OFF) : "memory");
}
template <int G>
__device__ __forceinline__ void stage_group(float (&o)[128], float i0, float i1, const uint32_t (&a)[4], uint32_t bar, bool lane0) {
    if (G < 16) {
#pragma unroll
        for (int i = 0; i < 8; i++) {
            o[8 * G + i] *= (i & 2) ? i1 : i0;
            asm volatile("" : "+f"(o[8 * G + i])::"memory");
        }
    }
    if (G >= 1) {
        constexpr int h = G - 1;
#pragma unroll
        for (int i = 0; i < 4; i++) o[8 * h + i] = __uint_as_float(pack_bf16(o[8 * h + 2 * i], o[8 * h + 2 * i + 1]));
        stsm_x4<(h >> 2) * 8192>(a[h & 3], o[8 * h], o[8 * h + 1], o[8 * h + 2], o[8 * h + 3]);
        if ((h & 3) == 3) {
            mbar_arrive_if(lane0, bar + 8 * (h >> 2));
        }
    }
    if (G < 16 && G % EPSP == EPSP - 1) sched_point();
    if constexpr (G < 16) stage_group<G + 1>(o, i0, i1, a, bar, lane0);
}
__device__ __forceinline__ void stage_addr(uint32_t (&a)[4], uint32_t dst) {
    const uint32_t lane = threadIdx.x & 31;
    const uint32_t row = ((threadIdx.x & 127) >> 5) * 16 + (lane & 15);
    const uint32_t x = ((lane >> 4) ^ (lane & 7)) << 4;
#pragma unroll
    for (int i = 0; i < 4; i++) a[i] = dst + row * 128 + (x ^ (i << 5));
    fence_regs(a);
}

__global__ void __launch_bounds__(384, 1)
gqa_kernel(const __grid_constant__ CUtensorMap map_q, const __grid_constant__ CUtensorMap map_k,
           const __grid_constant__ CUtensorMap map_v, const __grid_constant__ CUtensorMap map_o,
           const __grid_constant__ Sched sched, const uint8_t* __restrict__ qptr) {
    extern __shared__ __align__(1024) uint8_t smem[];
    const uint32_t slots = (uint32_t)__cvta_generic_to_shared(smem);
    const uint32_t bar_full = slots + kSlots * kSlotBytes;
    const uint32_t bar_empty = bar_full + 64;
    const uint32_t bar_staged = bar_full + 192;
    const uint32_t progress = bar_full + 160;
    const uint32_t bar_stored = bar_full + 144;

    const int six = blockIdx.x / 6;
    const int triple = TD(parity) ? six * 2 + (blockIdx.x & 1) : blockIdx.x / 3;
    const int sub = TD(parity) ? (blockIdx.x - six * 6) >> 1 : blockIdx.x - triple * 3;
    const int ntiles = (triple + 2 * kTriples < kPairs) ? 3 : 2;
    const int var = 3 - ntiles;
    const int wg = __shfl_sync(0xffffffffu, threadIdx.x >> 7, 0);

    uint64_t pol = 0, pol_kv = 0;
    auto issue_load = [&](uint32_t slot, uint32_t kind, uint32_t tile, uint32_t j) {
        const int pair = TD(samekv) ? triple % 4 : triple + tile * kTriples;
        const uint32_t bar = bar_full + 8 * slot, dst = slots + slot * kSlotBytes;
        mbar_expect_tx(bar, kSlotBytes);
        if (kind == 0) {
            const int row = pair * kRowsPerPair + sub * 128 + j * 64;
            if (TD(hint_q)) tma_load_hint(dst, &map_q, row, bar, pol); else tma_load(dst, &map_q, row, bar);
        } else {
            const int row = pair * kKeys + j * 64;
            const CUtensorMap* m = kind == 1 ? &map_k : &map_v;
            if (TD(hint_kv)) tma_load_hint(dst, m, row, bar, pol_kv); else tma_load(dst, m, row, bar);
        }
    };
    const uint32_t delay = (TD(start_delay) && var) ? TD(start_delay) : (blockIdx.x & 1) ? TD(odd_delay) : 0;
    const bool delayed = delay != 0;
    const uint32_t t_entry = clock32();

    if (threadIdx.x == 256) {
        asm volatile("prefetch.tensormap [%0];" ::"l"(&map_q) : "memory");
        asm volatile("prefetch.tensormap [%0];" ::"l"(&map_k) : "memory");
        asm volatile("prefetch.tensormap [%0];" ::"l"(&map_v) : "memory");
#pragma unroll
        for (int i = 0; i < kSlots; i++) mbar_init(bar_full + 8 * i, 1);
        asm volatile("fence.proxy.async.shared::cta;" ::: "memory");
        asm volatile("createpolicy.fractional.L2::evict_first.b64 %0, 1.0;" : "=l"(pol));
        asm volatile("createpolicy.fractional.L2::evict_first.b64 %0, %1;" : "=l"(pol_kv) : "f"(TD(kv_frac) * 0.01f));
        if (!delayed) {
            issue_load(0, 0, 0, 0);
            issue_load(1, 1, 0, 0);
            issue_load(2, 0, 0, 1);
        }
    } else if (threadIdx.x == 288) {
        if (slots & 1023) __trap();
#pragma unroll
        for (int i = 0; i < kSlots; i++) mbar_init(bar_empty + 8 * i, 8);
        asm volatile("st.volatile.shared.u32 [%0], %1;" ::"r"(progress), "r"(0) : "memory");
#pragma unroll
        for (int i = 0; i < 8; i++) mbar_init(bar_staged + 8 * i, 4);
        mbar_init(bar_stored, 1);
        mbar_init(bar_stored + 8, 1);
    }
    __syncthreads();

    if (wg == 2) {
        asm volatile("setmaxnreg.dec.sync.aligned.u32 40;");
        if (threadIdx.x == 256) {
            while (clock32() - t_entry < delay) __nanosleep(32);
            const int n = sched.nloads[var];
            for (int i = delayed ? 0 : 3; i < n; i++) {
                const uint32_t e = sched.prod[var][i];
                const uint32_t slot = e & 7, w = (e >> 10) & 3;
                if (w) mbar_wait(w == 1 ? bar_empty + 8 * slot : bar_stored + 8 * (w - 2), (e >> 12) & 1);
                issue_load(slot, (e >> 3) & 3, (e >> 5) & 3, (e >> 7) & 7);
                asm volatile("st.volatile.shared.u32 [%0], %1;" ::"r"(progress), "r"(i + 1) : "memory");
            }
        }
        else if (threadIdx.x >= 320 && threadIdx.x < 352) {
            const uint32_t lane = threadIdx.x & 31;
            for (int t = 1; t < ntiles; t++) {
                const uint8_t* a = qptr + (size_t)((triple + t * kTriples) * kRowsPerPair + sub * 128) * 512;
                const int first = t == 1 ? TD(qpf1) : TD(qpf2), cnt = t == 1 ? TD(qpfc1) : TD(qpfc2);
                for (int c = 0; c < cnt; c++) {
                    uint32_t pr;
                    int spins = 0;
                    while (true) {
                        asm volatile("ld.volatile.shared.u32 %0, [%1];" : "=r"(pr) : "r"(progress) : "memory");
                        if ((int)pr > first + c || ++spins > (1 << 20)) break;
                        __nanosleep(64);
                    }
                    for (uint32_t x = lane; x < TD(qpfl); x += 32) {
                        const uint32_t line = c * TD(qpfl) + x;
                        if (line < 512) asm volatile("prefetch.global.L2 [%0];" ::"l"(a + line * 128));
                    }
                }
            }
        }
        else if (threadIdx.x == 288) {
            for (int t = 0; t < ntiles; t++) {
                const uint32_t e = sched.cons[var][8 * t + 8];
                const int row = (triple + t * kTriples) * kRowsPerPair + sub * 128;
                const uint32_t gap = t == ntiles - 1 ? 0 : TD(stgap);
                uint32_t t0 = clock32() - gap;
#pragma unroll 1
                for (int w = 0; w < 2; w++) {
                    const uint32_t src = slots + ((e >> (16 + 4 * w)) & 7) * kSlotBytes;
#pragma unroll 1
                    for (int c = 0; c < 4; c++) {
                        mbar_wait(bar_staged + 32 * w + 8 * c, t & 1);
                        asm volatile("fence.proxy.async.shared::cta;" ::: "memory");
                        while (clock32() - t0 < gap) {}
                        t0 = clock32();
                        if (t >= TD(nostore)) tma_store(&map_o, src + c * 8192, row + w * 64, c);
                    }
                    asm volatile("cp.async.bulk.commit_group;" ::: "memory");
                    if (w == 0 && t == ntiles - 1) continue;
                    asm volatile("cp.async.bulk.wait_group.read 0;" ::: "memory");
                    mbar_arrive(bar_stored + 8 * w);
                }
            }
        }
    } else {
        asm volatile("setmaxnreg.inc.sync.aligned.u32 232;");
        const bool lane0 = (threadIdx.x & 31) == 0;
        const uint32_t kmaj_lo = (slots >> 4) | (1u << 16);
        const uint32_t nmaj_lo = (slots >> 4) | (512u << 16);
        const int my_turn = 1 + wg, other_turn = 2 - wg;
        float o[128], s[32];
        uint32_t p[16];
        float c0, c1, l0, l1, a0 = 1.f, a1 = 1.f;

        if (wg == 1) bar_arrive(1, 256);

        uint32_t e = sched.cons[var][0];
        uint32_t q_slot = (e >> (8 + 4 * wg)) & 7;
        mbar_wait(bar_full + 8 * q_slot, (e >> (11 + 4 * wg)) & 1);
        mbar_wait(bar_full + 8 * (e & 7), (e >> 3) & 1);
        TR(0, 0);
        bar_sync(my_turn, 256);
        TR(0, 1);
        wg_fence();
        issue_qk(s, kmaj_lo + q_slot * 2048, kmaj_lo + (e & 7) * 2048);
        bar_arrive(other_turn, 256);
        wg_wait<0>();
        fence_regs(s);
        mbar_arrive_if(lane0, bar_empty + 8 * (e & 7));
        softmax_first(s, c0, c1, l0, l1);
        pack_p(s, p);

        int g = 1;
        for (int t = 0;; t++) {
#pragma unroll 1
            for (int j = 1; j < 8; j++, g++) {
                e = sched.cons[var][g];
                const uint32_t ks = e & 7, vs = (e >> 4) & 7;
                mbar_wait(bar_full + 8 * ks, (e >> 3) & 1);
                TR(g, 0);
                bar_sync(my_turn, 256);
                TR(g, 1);
                fence_regs(o); fence_regs(p);
                wg_fence();
                issue_qk(s, kmaj_lo + q_slot * 2048, kmaj_lo + ks * 2048);
                mbar_wait(bar_full + 8 * vs, (e >> 7) & 1);
                TR(g, 2);
                wg_fence();
                issue_pv(o, p, nmaj_lo + vs * 2048, j > 1);
                bar_arrive(other_turn, 256);
                TR(g, 3);
                wg_wait<1>();
                fence_regs(s);
                TR(g, 4);
                mbar_arrive_if(lane0, bar_empty + 8 * ks);
                mbar_arrive2_if(lane0 && j == 7, bar_empty + 8 * q_slot);
                const bool rescale = softmax_next(s, c0, c1, l0, l1, a0, a1);
                fence_regs(s);
                asm volatile("" : "+f"(l0), "+f"(l1)::"memory");
                TR(g, 5);
                sched_point();
                wg_wait<0>();
                fence_regs(o); fence_regs(p);
                TR(g, 6);
                mbar_arrive_if(lane0, bar_empty + 8 * vs);
                if (rescale) {
#pragma unroll
                    for (int i = 0; i < 32; i++) {
                        o[4 * i] *= a0;
                        o[4 * i + 1] *= a0;
                        o[4 * i + 2] *= a1;
                        o[4 * i + 3] *= a1;
                        if (i % 2 == 1) { fence_regs(o); sched_point(); }
                    }
                }
                pack_p(s, p);
                TR(g, 7);
            }
            inv_row_sum(l0, l1, a0, a1);
            asm volatile("" : "+f"(a0), "+f"(a1)::"memory");
            if (t == ntiles - 1) break;
            e = sched.cons[var][g];
            const uint32_t ks = e & 7, vs = (e >> 4) & 7, os = (e >> (16 + 4 * wg)) & 7;
            q_slot = (e >> (8 + 4 * wg)) & 7;
            uint32_t oa[4];
            stage_addr(oa, slots + os * kSlotBytes);
            mbar_wait(bar_full + 8 * q_slot, (e >> (11 + 4 * wg)) & 1);
            mbar_wait(bar_full + 8 * ks, (e >> 3) & 1);
            TR(g, 0);
            bar_sync(my_turn, 256);
            TR(g, 1);
            fence_regs(o); fence_regs(p);
            wg_fence();
            issue_qk(s, kmaj_lo + q_slot * 2048, kmaj_lo + ks * 2048);
            mbar_wait(bar_full + 8 * vs, (e >> 7) & 1);
            TR(g, 2);
            wg_fence();
            issue_pv(o, p, nmaj_lo + vs * 2048, 1);
            bar_arrive(other_turn, 256);
            TR(g, 3);
            wg_wait<1>();
            fence_regs(s);
            TR(g, 4);
            mbar_arrive_if(lane0, bar_empty + 8 * ks);
            softmax_first(s, c0, c1, l0, l1);
            fence_regs(s);
            asm volatile("" : "+f"(l0), "+f"(l1)::"memory");
            TR(g, 5);
            sched_point();
            wg_wait<0>();
            fence_regs(o); fence_regs(p);
            TR(g, 6);
            mbar_arrive_if(lane0, bar_empty + 8 * vs);
            pack_p(s, p);
            mbar_wait(bar_empty + 8 * os, (e >> (19 + 4 * wg)) & 1);
            stage_group<0>(o, a0, a1, oa, bar_staged + 32 * wg, lane0);
            TR(g, 7);
            g++;
        }
        {
            e = sched.cons[var][g];
            const uint32_t vs = (e >> 4) & 7, os = (e >> (16 + 4 * wg)) & 7;
            uint32_t oa[4];
            stage_addr(oa, slots + os * kSlotBytes);
            mbar_wait(bar_full + 8 * vs, (e >> 7) & 1);
            TR(g, 0);
            bar_sync(my_turn, 256);
            TR(g, 1);
            fence_regs(o); fence_regs(p);
            wg_fence();
            issue_pv(o, p, nmaj_lo + vs * 2048, 1);
            if (wg == 0) bar_arrive(other_turn, 256);
            wg_wait<0>();
            fence_regs(o);
            TR(g, 6);
            mbar_arrive_if(lane0, bar_empty + 8 * vs);
            mbar_wait(bar_empty + 8 * os, (e >> (19 + 4 * wg)) & 1);
            stage_group<0>(o, a0, a1, oa, bar_staged + 32 * wg, lane0);
            TR(g, 7);
        }
    }
}

typedef CUresult (*EncodeTiledFn)(CUtensorMap*, CUtensorMapDataType, cuuint32_t, void*, const cuuint64_t*,
                                  const cuuint64_t*, const cuuint32_t*, const cuuint32_t*, CUtensorMapInterleave,
                                  CUtensorMapSwizzle, CUtensorMapL2promotion, CUtensorMapFloatOOBfill);

void make_map(EncodeTiledFn enc, CUtensorMap* m, void* ptr, uint64_t rows, uint32_t box_rows = 64, uint32_t box_chunks = 4) {
    cuuint64_t dims[3] = {64, rows, 4};
    cuuint64_t strides[2] = {512, 128};
    cuuint32_t box[3] = {64, box_rows, box_chunks};
    cuuint32_t es[3] = {1, 1, 1};
    enc(m, CU_TENSOR_MAP_DATA_TYPE_BFLOAT16, 3, ptr, dims, strides, box, es, CU_TENSOR_MAP_INTERLEAVE_NONE,
        CU_TENSOR_MAP_SWIZZLE_128B, CU_TENSOR_MAP_L2_PROMOTION_L2_128B, CU_TENSOR_MAP_FLOAT_OOB_FILL_NONE);
}

void build_sched(Sched* sc) {
    enum { Q = 0, K = 1, V = 2 };
    for (int var = 0; var < 2; var++) {
        const int nt = 3 - var;
        struct Item { int kind, tile, j; };
        Item loads[kMaxLoads], frees[kMaxLoads];
        int nl = 0, nf = 0;
        for (int t = 0; t < nt; t++) {
            loads[nl++] = {Q, t, 0};
            loads[nl++] = {K, t, 0};
            if (t) loads[nl++] = {V, t - 1, 7};
            loads[nl++] = {Q, t, 1};
            for (int j = 1; j < 8; j++) {
                loads[nl++] = {K, t, j};
                loads[nl++] = {V, t, j - 1};
            }
        }
        loads[nl++] = {V, nt - 1, 7};
        for (int t = 0; t < nt; t++) {
            int pos = 0;
            auto push = [&](Item it) {
                if (t && pos == TH(o0pos)) frees[nf++] = {V, t - 1, 6};
                if (t && pos == TH(o1pos)) frees[nf++] = {V, t - 1, 7};
                frees[nf++] = it;
                pos++;
            };
            push({K, t, 0});
            for (int j = 1; j < 7; j++) {
                push({K, t, j});
                push({V, t, j - 1});
            }
            push({Q, t, 0});
            push({K, t, 7});
            push({Q, t, 1});
        }
        int slot_of[3][3][8], use_of[3][3][8], uses[kSlots] = {0};
        for (int i = 0; i < nl; i++) {
            int slot, wait = 0, par = 0;
            if (i < kSlots) {
                slot = i;
            } else {
                const Item f = frees[i - kSlots];
                slot = slot_of[f.kind][f.tile][f.j];
                if (f.kind == V && f.j >= 6) {
                    wait = 2 + (f.j - 6);
                    par = f.tile & 1;
                } else {
                    wait = 1;
                    par = use_of[f.kind][f.tile][f.j] & 1;
                }
            }
            const Item l = loads[i];
            slot_of[l.kind][l.tile][l.j] = slot;
            use_of[l.kind][l.tile][l.j] = uses[slot]++;
            sc->prod[var][i] = slot | l.kind << 3 | l.tile << 5 | l.j << 7 | wait << 10 | par << 12;
        }
        sc->nloads[var] = nl;
        auto nib = [&](int kind, int t, int j) { return (uint32_t)(slot_of[kind][t][j] | (use_of[kind][t][j] & 1) << 3); };
        for (int g = 0; g <= 8 * nt; g++) {
            const int t = g / 8, j = g % 8;
            uint32_t e = 0;
            if (t < nt) e |= nib(K, t, j);
            if (g > 0) e |= nib(V, (g - 1) / 8, (g - 1) % 8) << 4;
            if (j == 0 && t < nt) e |= nib(Q, t, 0) << 8 | nib(Q, t, 1) << 12;
            if (j == 0 && t > 0) e |= nib(V, t - 1, 6) << 16 | nib(V, t - 1, 7) << 20;
            sc->cons[var][g] = e;
        }
    }
}

}

extern "C" void kernel_launch(void* const* d_in, const int* in_sizes, int n_in, void* d_out, int out_size) {
    (void)in_sizes; (void)n_in; (void)out_size;
    static EncodeTiledFn enc = nullptr;
    static Sched sched;
    if (!enc) {
        void* fn = nullptr;
        cudaDriverEntryPointQueryResult qr;
        cudaGetDriverEntryPoint("cuTensorMapEncodeTiled", &fn, cudaEnableDefault, &qr);
        enc = (EncodeTiledFn)fn;
        build_sched(&sched);
        cudaFuncSetAttribute(gqa_kernel, cudaFuncAttributeMaxDynamicSharedMemorySize, kSmemBytes);
    }
    CUtensorMap mq, mk, mv, mo;
    make_map(enc, &mq, d_in[0], (uint64_t)kPairs * kRowsPerPair);
    make_map(enc, &mk, d_in[1], (uint64_t)kPairs * kKeys);
    make_map(enc, &mv, d_in[2], (uint64_t)kPairs * kKeys);
    make_map(enc, &mo, d_out, (uint64_t)kPairs * kRowsPerPair, 64, 1);
    gqa_kernel<<<GRID, 384, kSmemBytes, cudaStreamPerThread>>>(mq, mk, mv, mo, sched, (const uint8_t*)d_in[0]);
}
```

```cpp
#include <cuda_runtime.h>
#include <cuda_bf16.h>
#include <cuda.h>
#include <stdint.h>

#define INLINE __attribute__((always_inline))

namespace {

constexpr int kGrid = 132;
constexpr int kPairs = 128;
constexpr int kRowsPerPair = 384;
constexpr int kKeys = 512;
constexpr int kSlots = 7;
constexpr int kSlotBytes = 32768;
constexpr int kSmemBytes = kSlots * kSlotBytes + 256;
constexpr int kMaxLoads = 60;

constexpr int kBarFull = 0;
constexpr int kBarEmpty = 64;
constexpr int kBarQLo = 128;
constexpr int kBarStored = 144;
constexpr int kBarQHi = 160;
constexpr int kBarStaged = 192;

constexpr int kShortPos = 5;
constexpr int kShortDelay = 15000;
constexpr int kEarlyLines = 256;
constexpr int kPace0 = 1400, kPace = 360;
constexpr int kStoreRows = 32, kStoreNs0 = 100, kStoreNs1 = 200;
constexpr int kStored0Pos = 4, kStored1Pos = 8;
constexpr int kQPos[2][4] = {{12, 12, 14, 14}, {15, 15, 14, 14}};
constexpr int kPf[2][3] = {{9, 15, 4}, {25, 29, 6}};
constexpr int kExpBeforePv = 2, kExpBeforePvLast = 1;
constexpr int kEpi1 = 3, kEpi2 = 7, kEpi3 = 11;
constexpr int kFill5 = 1, kFill6 = 2;

struct Maps {
    CUtensorMap q, k, v, o, o_piece;
};

struct alignas(64) ConsumerSched {
    uint64_t kv[3];
    uint64_t desc_hi;
    uint32_t qo[4];
};
struct Sched {
    ConsumerSched cons[2];
    uint4 load[2][kMaxLoads];
};


__device__ __forceinline__ void mbar_init(uint32_t bar, uint32_t cnt) {
    asm volatile("mbarrier.init.shared::cta.b64 [%0], %1;" ::"r"(bar), "r"(cnt) : "memory");
}
__device__ __forceinline__ void mbar_expect_tx(uint32_t bar, uint32_t bytes) {
    asm volatile("mbarrier.arrive.expect_tx.shared::cta.b64 _, [%0], %1;" ::"r"(bar), "r"(bytes) : "memory");
}
__device__ __forceinline__ void mbar_arrive(uint32_t bar) {
    asm volatile("mbarrier.arrive.shared::cta.b64 _, [%0];" ::"r"(bar) : "memory");
}
__device__ __forceinline__ void mbar_arrive_if(bool pred, uint32_t bar) {
    asm volatile("{ .reg .pred p; setp.ne.u32 p, %1, 0; @p mbarrier.arrive.shared::cta.b64 _, [%0]; }"
                 ::"r"(bar), "r"((uint32_t)pred) : "memory");
}
__device__ __forceinline__ bool mbar_test(uint32_t bar, uint32_t parity) {
    uint32_t ok;
    asm volatile("{ .reg .pred p; mbarrier.test_wait.parity.shared::cta.b64 p, [%1], %2; selp.u32 %0, 1, 0, p; }"
                 : "=r"(ok) : "r"(bar), "r"(parity) : "memory");
    return ok;
}
__device__ __forceinline__ void mbar_wait(uint32_t bar, uint32_t parity) {
    asm volatile(
        "{\n"
        ".reg .pred p, q;\n"
        ".reg .u32 n;\n"
        "mbarrier.try_wait.parity.shared::cta.b64 p, [%0], %1;\n"
        "@p bra DONE;\n"
        "mov.u32 n, 0;\n"
        "LOOP:\n"
        "mbarrier.try_wait.parity.shared::cta.b64 p, [%0], %1;\n"
        "@p bra DONE;\n"
        "add.u32 n, n, 1;\n"
        "setp.lt.u32 q, n, 67108864;\n"
        "@q bra LOOP;\n"
        "trap;\n"
        "DONE:\n"
        "}\n" ::"r"(bar), "r"(parity) : "memory");
}
__device__ __forceinline__ void mbar_wait_relaxed(uint32_t bar, uint32_t parity) {
    asm volatile(
        "{\n"
        ".reg .pred p, q;\n"
        ".reg .u32 n;\n"
        "mov.u32 n, 0;\n"
        "LOOP:\n"
        "mbarrier.try_wait.parity.shared::cta.b64 p, [%0], %1, %2;\n"
        "@p bra DONE;\n"
        "add.u32 n, n, 1;\n"
        "setp.lt.u32 q, n, 524288;\n"
        "@q bra LOOP;\n"
        "trap;\n"
        "DONE:\n"
        "}\n" ::"r"(bar), "r"(parity), "r"(4000) : "memory");
}
__device__ __forceinline__ bool elect_one() {
    uint32_t p;
    asm volatile("{ .reg .pred p; elect.sync _|p, 0xffffffff; selp.u32 %0, 1, 0, p; }" : "=r"(p));
    return p;
}
__device__ __forceinline__ void tma_load(uint32_t dst, const CUtensorMap* m, int row, int chunk, uint32_t bar, uint64_t pol) {
    asm volatile(
        "cp.async.bulk.tensor.3d.shared::cluster.global.mbarrier::complete_tx::bytes.L2::cache_hint [%0], [%1, {%3, %4, %6}], [%2], %5;"
        ::"r"(dst), "l"(m), "r"(bar), "r"(0), "r"(row), "l"(pol), "r"(chunk) : "memory");
}
__device__ __forceinline__ void tma_store(const CUtensorMap* m, uint32_t src, int row, int chunk) {
    asm volatile("cp.async.bulk.tensor.3d.global.shared::cta.bulk_group [%0, {%2, %3, %4}], [%1];"
                 ::"l"(m), "r"(src), "r"(0), "r"(row), "r"(chunk) : "memory");
}
__device__ __forceinline__ void prefetch_map(const CUtensorMap* m) {
    asm volatile("prefetch.tensormap [%0];" ::"l"(m) : "memory");
}
__device__ __forceinline__ uint32_t clock32() {
    uint32_t t;
    asm volatile("mov.u32 %0, %%clock;" : "=r"(t));
    return t;
}
__device__ __forceinline__ void wg_fence() { asm volatile("wgmma.fence.sync.aligned;" ::: "memory"); }
__device__ __forceinline__ void wg_commit() { asm volatile("wgmma.commit_group.sync.aligned;" ::: "memory"); }
template <int N>
__device__ __forceinline__ void wg_wait() { asm volatile("wgmma.wait_group.sync.aligned %0;" ::"n"(N) : "memory"); }
template <int n>
__device__ __forceinline__ void fence_regs(float (&r)[n]) {
#pragma unroll
    for (int i = 0; i < n; i++) asm volatile("" : "+f"(r[i])::"memory");
}
template <int n>
__device__ __forceinline__ void fence_regs(uint32_t (&r)[n]) {
#pragma unroll
    for (int i = 0; i < n; i++) asm volatile("" : "+r"(r[i])::"memory");
}
__device__ __forceinline__ void bar_sync(int id, int n) { asm volatile("bar.sync %0, %1;" ::"r"(id), "r"(n) : "memory"); }
__device__ __forceinline__ void bar_arrive(int id, int n) { asm volatile("bar.arrive %0, %1;" ::"r"(id), "r"(n) : "memory"); }
__device__ __forceinline__ void sched_point() { asm volatile("pmevent 0;" ::: "memory"); }
__device__ __forceinline__ float ex2(float x) {
    float y;
    asm("ex2.approx.ftz.f32 %0, %1;" : "=f"(y) : "f"(x));
    return y;
}
__device__ __forceinline__ uint32_t pack_bf16(float lo, float hi) {
    uint32_t r;
    asm("cvt.rn.bf16x2.f32 %0, %1, %2;" : "=r"(r) : "f"(hi), "f"(lo));
    return r;
}
__device__ __forceinline__ void ldsm_x4(uint32_t addr, uint32_t& r0, uint32_t& r1, uint32_t& r2, uint32_t& r3) {
    asm volatile("ldmatrix.sync.aligned.m8n8.x4.shared.b16 {%0, %1, %2, %3}, [%4];"
                 : "=r"(r0), "=r"(r1), "=r"(r2), "=r"(r3) : "r"(addr) : "memory");
}
template <int OFF>
__device__ __forceinline__ void stsm_x4(uint32_t addr, float r0, float r1, float r2, float r3) {
    asm volatile("stmatrix.sync.aligned.m8n8.x4.shared.b16 [%0 + %5], {%1, %2, %3, %4};"
                 ::"r"(addr), "r"(__float_as_uint(r0)), "r"(__float_as_uint(r1)), "r"(__float_as_uint(r2)),
                   "r"(__float_as_uint(r3)), "n"(OFF) : "memory");
}

template <int C>
__device__ __forceinline__ void wgmma_rs_n64_tb(float (&d)[128], uint32_t a0, uint32_t a1, uint32_t a2, uint32_t a3, uint64_t db) {
    asm volatile("{ .reg .pred p; setp.ne.b32 p, 1, 0;\n"
        "wgmma.mma_async.sync.aligned.m64n64k16.f32.bf16.bf16 "
        "{%0, %1, %2, %3, %4, %5, %6, %7, %8, %9, %10, %11, %12, %13, %14, %15, %16, %17, %18, %19, %20, %21, %22, %23, %24, %25, %26, %27, %28, %29, %30, %31}, "
        "{%32, %33, %34, %35}, %36, p, 1, 1, 1; }\n"
        : "+f"(d[32 * C + 0]), "+f"(d[32 * C + 1]), "+f"(d[32 * C + 2]), "+f"(d[32 * C + 3]), "+f"(d[32 * C + 4]), "+f"(d[32 * C + 5]), "+f"(d[32 * C + 6]), "+f"(d[32 * C + 7]),
          "+f"(d[32 * C + 8]), "+f"(d[32 * C + 9]), "+f"(d[32 * C + 10]), "+f"(d[32 * C + 11]), "+f"(d[32 * C + 12]), "+f"(d[32 * C + 13]), "+f"(d[32 * C + 14]), "+f"(d[32 * C + 15]),
          "+f"(d[32 * C + 16]), "+f"(d[32 * C + 17]), "+f"(d[32 * C + 18]), "+f"(d[32 * C + 19]), "+f"(d[32 * C + 20]), "+f"(d[32 * C + 21]), "+f"(d[32 * C + 22]), "+f"(d[32 * C + 23]),
          "+f"(d[32 * C + 24]), "+f"(d[32 * C + 25]), "+f"(d[32 * C + 26]), "+f"(d[32 * C + 27]), "+f"(d[32 * C + 28]), "+f"(d[32 * C + 29]), "+f"(d[32 * C + 30]), "+f"(d[32 * C + 31])
        : "r"(a0), "r"(a1), "r"(a2), "r"(a3), "l"(db));
}

template <int SCALE_D>
__device__ __forceinline__ void wgmma_rs_n64(float (&d)[32], uint32_t a0, uint32_t a1, uint32_t a2, uint32_t a3, uint64_t db) {
    asm volatile("{ .reg .pred p; setp.ne.b32 p, %37, 0;\n"
        "wgmma.mma_async.sync.aligned.m64n64k16.f32.bf16.bf16 "
        "{%0, %1, %2, %3, %4, %5, %6, %7, %8, %9, %10, %11, %12, %13, %14, %15, %16, %17, %18, %19, %20, %21, %22, %23, %24, %25, %26, %27, %28, %29, %30, %31}, "
        "{%32, %33, %34, %35}, %36, p, 1, 1, 0; }\n"
        : "+f"(d[0]), "+f"(d[1]), "+f"(d[2]), "+f"(d[3]), "+f"(d[4]), "+f"(d[5]), "+f"(d[6]), "+f"(d[7]), "+f"(d[8]), "+f"(d[9]), "+f"(d[10]), "+f"(d[11]), "+f"(d[12]), "+f"(d[13]), "+f"(d[14]), "+f"(d[15]), "+f"(d[16]), "+f"(d[17]), "+f"(d[18]), "+f"(d[19]), "+f"(d[20]), "+f"(d[21]), "+f"(d[22]), "+f"(d[23]), "+f"(d[24]), "+f"(d[25]), "+f"(d[26]), "+f"(d[27]), "+f"(d[28]), "+f"(d[29]), "+f"(d[30]), "+f"(d[31])
        : "r"(a0), "r"(a1), "r"(a2), "r"(a3), "l"(db), "n"(SCALE_D));
}

template <int SCALE_D>
__device__ __forceinline__ void wgmma_ss_n64(float (&d)[32], uint64_t da, uint64_t db) {
    asm volatile("{ .reg .pred p; setp.ne.b32 p, %34, 0;\n"
        "wgmma.mma_async.sync.aligned.m64n64k16.f32.bf16.bf16 "
        "{%0, %1, %2, %3, %4, %5, %6, %7, %8, %9, %10, %11, %12, %13, %14, %15, %16, %17, %18, %19, %20, %21, %22, %23, %24, %25, %26, %27, %28, %29, %30, %31}, "
        "%32, %33, p, 1, 1, 0, 0; }\n"
        : "+f"(d[0]), "+f"(d[1]), "+f"(d[2]), "+f"(d[3]), "+f"(d[4]), "+f"(d[5]), "+f"(d[6]), "+f"(d[7]), "+f"(d[8]), "+f"(d[9]), "+f"(d[10]), "+f"(d[11]), "+f"(d[12]), "+f"(d[13]), "+f"(d[14]), "+f"(d[15]), "+f"(d[16]), "+f"(d[17]), "+f"(d[18]), "+f"(d[19]), "+f"(d[20]), "+f"(d[21]), "+f"(d[22]), "+f"(d[23]), "+f"(d[24]), "+f"(d[25]), "+f"(d[26]), "+f"(d[27]), "+f"(d[28]), "+f"(d[29]), "+f"(d[30]), "+f"(d[31])
        : "l"(da), "l"(db), "n"(SCALE_D));
}
__device__ __forceinline__ void wgmma_ss_n64_rt(float (&d)[32], uint64_t da, uint64_t db, int scale_d) {
    asm volatile("{ .reg .pred p; setp.ne.b32 p, %34, 0;\n"
        "wgmma.mma_async.sync.aligned.m64n64k16.f32.bf16.bf16 "
        "{%0, %1, %2, %3, %4, %5, %6, %7, %8, %9, %10, %11, %12, %13, %14, %15, %16, %17, %18, %19, %20, %21, %22, %23, %24, %25, %26, %27, %28, %29, %30, %31}, "
        "%32, %33, p, 1, 1, 0, 0; }\n"
        : "+f"(d[0]), "+f"(d[1]), "+f"(d[2]), "+f"(d[3]), "+f"(d[4]), "+f"(d[5]), "+f"(d[6]), "+f"(d[7]), "+f"(d[8]), "+f"(d[9]), "+f"(d[10]), "+f"(d[11]), "+f"(d[12]), "+f"(d[13]), "+f"(d[14]), "+f"(d[15]), "+f"(d[16]), "+f"(d[17]), "+f"(d[18]), "+f"(d[19]), "+f"(d[20]), "+f"(d[21]), "+f"(d[22]), "+f"(d[23]), "+f"(d[24]), "+f"(d[25]), "+f"(d[26]), "+f"(d[27]), "+f"(d[28]), "+f"(d[29]), "+f"(d[30]), "+f"(d[31])
        : "l"(da), "l"(db), "r"(scale_d));
}

__device__ __forceinline__ void wgmma_rs_n256_tb(float (&d)[128], uint32_t a0, uint32_t a1, uint32_t a2, uint32_t a3, uint64_t db, int scale_d) {
    asm volatile("{ .reg .pred p; setp.ne.b32 p, %133, 0;\n"
        "wgmma.mma_async.sync.aligned.m64n256k16.f32.bf16.bf16 "
        "{%0, %1, %2, %3, %4, %5, %6, %7, %8, %9, %10, %11, %12, %13, %14, %15, "
        "%16, %17, %18, %19, %20, %21, %22, %23, %24, %25, %26, %27, %28, %29, %30, %31, "
        "%32, %33, %34, %35, %36, %37, %38, %39, %40, %41, %42, %43, %44, %45, %46, %47, "
        "%48, %49, %50, %51, %52, %53, %54, %55, %56, %57, %58, %59, %60, %61, %62, %63, "
        "%64, %65, %66, %67, %68, %69, %70, %71, %72, %73, %74, %75, %76, %77, %78, %79, "
        "%80, %81, %82, %83, %84, %85, %86, %87, %88, %89, %90, %91, %92, %93, %94, %95, "
        "%96, %97, %98, %99, %100, %101, %102, %103, %104, %105, %106, %107, %108, %109, %110, %111, "
        "%112, %113, %114, %115, %116, %117, %118, %119, %120, %121, %122, %123, %124, %125, %126, %127}, "
        "{%128, %129, %130, %131}, %132, p, 1, 1, 1; }\n"
        : "+f"(d[0]), "+f"(d[1]), "+f"(d[2]), "+f"(d[3]), "+f"(d[4]), "+f"(d[5]), "+f"(d[6]), "+f"(d[7]),
          "+f"(d[8]), "+f"(d[9]), "+f"(d[10]), "+f"(d[11]), "+f"(d[12]), "+f"(d[13]), "+f"(d[14]), "+f"(d[15]),
          "+f"(d[16]), "+f"(d[17]), "+f"(d[18]), "+f"(d[19]), "+f"(d[20]), "+f"(d[21]), "+f"(d[22]), "+f"(d[23]),
          "+f"(d[24]), "+f"(d[25]), "+f"(d[26]), "+f"(d[27]), "+f"(d[28]), "+f"(d[29]), "+f"(d[30]), "+f"(d[31]),
          "+f"(d[32]), "+f"(d[33]), "+f"(d[34]), "+f"(d[35]), "+f"(d[36]), "+f"(d[37]), "+f"(d[38]), "+f"(d[39]),
          "+f"(d[40]), "+f"(d[41]), "+f"(d[42]), "+f"(d[43]), "+f"(d[44]), "+f"(d[45]), "+f"(d[46]), "+f"(d[47]),
          "+f"(d[48]), "+f"(d[49]), "+f"(d[50]), "+f"(d[51]), "+f"(d[52]), "+f"(d[53]), "+f"(d[54]), "+f"(d[55]),
          "+f"(d[56]), "+f"(d[57]), "+f"(d[58]), "+f"(d[59]), "+f"(d[60]), "+f"(d[61]), "+f"(d[62]), "+f"(d[63]),
          "+f"(d[64]), "+f"(d[65]), "+f"(d[66]), "+f"(d[67]), "+f"(d[68]), "+f"(d[69]), "+f"(d[70]), "+f"(d[71]),
          "+f"(d[72]), "+f"(d[73]), "+f"(d[74]), "+f"(d[75]), "+f"(d[76]), "+f"(d[77]), "+f"(d[78]), "+f"(d[79]),
          "+f"(d[80]), "+f"(d[81]), "+f"(d[82]), "+f"(d[83]), "+f"(d[84]), "+f"(d[85]), "+f"(d[86]), "+f"(d[87]),
          "+f"(d[88]), "+f"(d[89]), "+f"(d[90]), "+f"(d[91]), "+f"(d[92]), "+f"(d[93]), "+f"(d[94]), "+f"(d[95]),
          "+f"(d[96]), "+f"(d[97]), "+f"(d[98]), "+f"(d[99]), "+f"(d[100]), "+f"(d[101]), "+f"(d[102]), "+f"(d[103]),
          "+f"(d[104]), "+f"(d[105]), "+f"(d[106]), "+f"(d[107]), "+f"(d[108]), "+f"(d[109]), "+f"(d[110]), "+f"(d[111]),
          "+f"(d[112]), "+f"(d[113]), "+f"(d[114]), "+f"(d[115]), "+f"(d[116]), "+f"(d[117]), "+f"(d[118]), "+f"(d[119]),
          "+f"(d[120]), "+f"(d[121]), "+f"(d[122]), "+f"(d[123]), "+f"(d[124]), "+f"(d[125]), "+f"(d[126]), "+f"(d[127])
        : "r"(a0), "r"(a1), "r"(a2), "r"(a3), "l"(db), "r"(scale_d));
}


template <int K>
struct Idx { static constexpr int value = K; };

template <int K, typename F>
__device__ __forceinline__ void issue_qk(float (&s)[32], const uint32_t (&q)[32], uint64_t q_desc, uint64_t k_desc, F side) {
    constexpr int k = K >> 1;
    constexpr uint32_t off = ((k >> 2) * 8192 + (k & 3) * 32) >> 4;
    if (!(K & 1)) wgmma_ss_n64<(K > 0)>(s, q_desc + off, k_desc + 1024 + off);
    else wgmma_rs_n64<1>(s, q[4 * k], q[4 * k + 1], q[4 * k + 2], q[4 * k + 3], k_desc + off);
    if (K == 15) wg_commit();
    side(Idx<K>());
    if constexpr (K < 15) issue_qk<K + 1>(s, q, q_desc, k_desc, side);
}
__device__ __forceinline__ void issue_pv(float (&o)[128], uint32_t (&p)[16], uint64_t v_desc, int accumulate) {
#pragma unroll
    for (int k = 0; k < 4; k++)
        wgmma_rs_n256_tb(o, p[4 * k], p[4 * k + 1], p[4 * k + 2], p[4 * k + 3], v_desc + k * 128, k ? 1 : accumulate);
    wg_commit();
}


constexpr float kScaleLog2 = 0.0625f * 1.4426950408889634f;
constexpr float kSlack = 8.0f;

__device__ __forceinline__ void row_max(const float (&s)[32], float& x0, float& x1) {
    x0 = fmaxf(s[0], s[1]);
    x1 = fmaxf(s[2], s[3]);
    float y0 = fmaxf(s[4], s[5]), y1 = fmaxf(s[6], s[7]);
#pragma unroll
    for (int i = 2; i < 8; i += 2) {
        x0 = fmaxf(x0, fmaxf(s[4 * i], s[4 * i + 1]));
        x1 = fmaxf(x1, fmaxf(s[4 * i + 2], s[4 * i + 3]));
        y0 = fmaxf(y0, fmaxf(s[4 * i + 4], s[4 * i + 5]));
        y1 = fmaxf(y1, fmaxf(s[4 * i + 6], s[4 * i + 7]));
    }
    x0 = fmaxf(x0, y0);
    x1 = fmaxf(x1, y1);
    x0 = fmaxf(x0, __shfl_xor_sync(0xffffffffu, x0, 1));
    x1 = fmaxf(x1, __shfl_xor_sync(0xffffffffu, x1, 1));
    x0 = fmaxf(x0, __shfl_xor_sync(0xffffffffu, x0, 2));
    x1 = fmaxf(x1, __shfl_xor_sync(0xffffffffu, x1, 2));
}
__device__ __forceinline__ int score_limit(float c) {
    return max(__float_as_int((kSlack - c) * (0.9999995f / kScaleLog2)), -1);
}
__device__ __forceinline__ void set_max(const float (&s)[32], float& c0, float& c1, int& t0, int& t1) {
    float x0, x1;
    row_max(s, x0, x1);
    c0 = -x0 * kScaleLog2;
    c1 = -x1 * kScaleLog2;
    t0 = score_limit(c0);
    t1 = score_limit(c1);
}
__device__ __forceinline__ bool over_limit(const float (&s)[32], int t0, int t1) {
    int m0 = 0, m1 = 0;
#pragma unroll
    for (int i = 0; i < 8; i++) {
        m0 = __vimax3_s32(m0, __float_as_int(s[4 * i]), __float_as_int(s[4 * i + 1]));
        m1 = __vimax3_s32(m1, __float_as_int(s[4 * i + 2]), __float_as_int(s[4 * i + 3]));
    }
    return m0 > t0 || m1 > t1;
}
__device__ __forceinline__ void raise_max(const float (&s)[32], float& c0, float& c1, int& t0, int& t1, float& a0, float& a1) {
    float x0, x1;
    row_max(s, x0, x1);
    x0 = fminf(-x0 * kScaleLog2, c0);
    x1 = fminf(-x1 * kScaleLog2, c1);
    a0 = ex2(x0 - c0);
    a1 = ex2(x1 - c1);
    c0 = x0;
    c1 = x1;
    t0 = score_limit(c0);
    t1 = score_limit(c1);
}
__device__ __forceinline__ void rescale_o(float (&o)[128], float a0, float a1) {
#pragma unroll
    for (int i = 0; i < 32; i++) {
        o[4 * i] *= a0;
        o[4 * i + 1] *= a0;
        o[4 * i + 2] *= a1;
        o[4 * i + 3] *= a1;
        if (i % 2 == 1) { fence_regs(o); sched_point(); }
    }
}
template <int n>
__device__ __forceinline__ void rescale_p(uint32_t (&p)[n], float a0, float a1) {
#pragma unroll
    for (int i = 0; i < n; i++) {
        const float a = (i & 1) ? a1 : a0;
        p[i] = pack_bf16(__uint_as_float(p[i] << 16) * a, __uint_as_float(p[i] & 0xffff0000u) * a);
        asm volatile("" : "+r"(p[i])::"memory");
        if (i % 2 == 1) sched_point();
    }
}
template <int A, int B, typename F>
__device__ __forceinline__ void exp_groups(float (&s)[32], float c0, float c1, F side) {
    if (A == 0 && B > 0) {
#pragma unroll
        for (int i = 0; i < 4; i++) s[i] = fmaf(s[i], kScaleLog2, (i & 2) ? c1 : c0);
        fence_regs(s);
        sched_point();
    }
#pragma unroll
    for (int g = A; g < B; g++) {
        if (g == 4) side();
#pragma unroll
        for (int i = 4 * g; i < 4 * g + 4; i++) s[i] = ex2(s[i]);
#pragma unroll
        for (int i = 4 + 8 * g; i < 12 + 8 * g && i < 32; i++) s[i] = fmaf(s[i], kScaleLog2, (i & 2) ? c1 : c0);
        if (g < 4 || g == B - 1) {
            fence_regs(s);
            sched_point();
        }
    }
}
template <typename F>
__device__ __forceinline__ void exp_pipelined(float (&s)[32], float c0, float c1, F done) {
#pragma unroll
    for (int i = 0; i < 4; i++) s[i] = fmaf(s[i], kScaleLog2, (i & 2) ? c1 : c0);
    fence_regs(s);
    sched_point();
#pragma unroll
    for (int g = 0; g < 8; g++) {
        if (g == 3) done(Idx<0>());
        if (g == 5) done(Idx<1>());
        if (g == 7) done(Idx<2>());
#pragma unroll
        for (int i = 4 * g; i < 4 * g + 4; i++) s[i] = ex2(s[i]);
#pragma unroll
        for (int i = 4 + 8 * g; i < 12 + 8 * g && i < 32; i++) s[i] = fmaf(s[i], kScaleLog2, (i & 2) ? c1 : c0);
        if (g != 3 && g != 5) {
            fence_regs(s);
            sched_point();
        }
    }
    done(Idx<3>());
}
template <int N>
__device__ __forceinline__ void sum_groups(const float (&s)[32], float& r0, float& r1) {
    float u0 = s[1], u1 = s[3];
    r0 = s[0];
    r1 = s[2];
#pragma unroll
    for (int i = 1; i < N; i++) {
        r0 += s[4 * i];
        u0 += s[4 * i + 1];
        r1 += s[4 * i + 2];
        u1 += s[4 * i + 3];
    }
    r0 += u0;
    r1 += u1;
    asm volatile("" : "+f"(r0), "+f"(r1)::"memory");
}
__device__ __forceinline__ void pack_and_sum(const float (&s)[32], uint32_t (&p)[16], float& l0, float& l1, float r0, float r1) {
#pragma unroll
    for (int h = 0; h < 4; h++) {
#pragma unroll
        for (int i = 4 * h; i < 4 * h + 4; i++) p[i] = pack_bf16(s[2 * i], s[2 * i + 1]);
#pragma unroll
        for (int i = 3 + h * 5 / 4; i < 3 + (h + 1) * 5 / 4; i++) {
            r0 += s[4 * i];
            l0 += s[4 * i + 1];
            r1 += s[4 * i + 2];
            l1 += s[4 * i + 3];
        }
        if (h < 3) {
            asm volatile("" : "+f"(l0), "+f"(l1), "+f"(r0), "+f"(r1), "+r"(p[4 * h]), "+r"(p[4 * h + 1]),
                              "+r"(p[4 * h + 2]), "+r"(p[4 * h + 3])::"memory");
            sched_point();
        }
    }
    l0 += r0;
    l1 += r1;
}
__device__ __forceinline__ void inv_row_sum(float& i0, float& i1) {
#pragma unroll
    for (int m = 1; m <= 2; m++) {
        i0 += __shfl_xor_sync(0xffffffffu, i0, m);
        i1 += __shfl_xor_sync(0xffffffffu, i1, m);
        asm volatile("" : "+f"(i0), "+f"(i1)::"memory");
    }
    asm("rcp.approx.ftz.f32 %0, %0;" : "+f"(i0));
    asm("rcp.approx.ftz.f32 %0, %0;" : "+f"(i1));
    asm volatile("" : "+f"(i0), "+f"(i1)::"memory");
}


__device__ __forceinline__ void tile_addr(uint32_t (&a)[4], uint32_t tile) {
    const uint32_t lane = threadIdx.x & 31;
    const uint32_t row = ((threadIdx.x & 127) >> 5) * 16 + (lane & 15);
    const uint32_t x = ((lane >> 4) ^ (lane & 7)) << 4;
#pragma unroll
    for (int i = 0; i < 4; i++) a[i] = tile + row * 128 + (x ^ (i << 5));
    fence_regs(a);
}
__device__ __forceinline__ void load_q(uint32_t (&q)[32], const uint32_t (&a)[4]) {
#pragma unroll
    for (int k = 0; k < 8; k++) ldsm_x4(a[k & 3] + (k >> 2) * 8192, q[4 * k], q[4 * k + 1], q[4 * k + 2], q[4 * k + 3]);
    fence_regs(q);
}
__device__ __forceinline__ uint32_t after_load_q(const uint32_t (&q)[32], uint32_t zero) {
    return (q[0] | q[4] | q[8] | q[12] | q[16] | q[20] | q[24] | q[28]) & zero;
}
template <int G, int END>
__device__ __forceinline__ void stage_groups(float (&o)[128], float i0, float i1, const uint32_t (&a)[4], uint32_t bar, bool lane0) {
    constexpr int h = G - 1;
#pragma unroll
    for (int half = 0; half < 2; half++) {
        if (G < 16) {
#pragma unroll
            for (int i = 4 * half; i < 4 * half + 4; i++) {
                o[8 * G + i] *= (i & 2) ? i1 : i0;
                asm volatile("" : "+f"(o[8 * G + i])::"memory");
            }
        }
        if (G >= 1) {
#pragma unroll
            for (int i = 2 * half; i < 2 * half + 2; i++)
                o[8 * h + i] = __uint_as_float(pack_bf16(o[8 * h + 2 * i], o[8 * h + 2 * i + 1]));
        }
        if (half == 0 && G >= 1) {
            asm volatile("" : "+f"(o[8 * h]), "+f"(o[8 * h + 1])::"memory");
            sched_point();
        }
    }
    if constexpr (G >= 1) {
        stsm_x4<(h >> 2) * 8192>(a[h & 3], o[8 * h], o[8 * h + 1], o[8 * h + 2], o[8 * h + 3]);
        if ((h & 3) == 3) {
            __syncwarp();
            mbar_arrive_if(lane0, bar + 8 * (h >> 2));
        }
    }
    if (G < 16) sched_point();
    if constexpr (G + 1 < END) stage_groups<G + 1, END>(o, i0, i1, a, bar, lane0);
}
template <int C, int H>
__device__ __forceinline__ void stage_half(float (&o)[128], float i0, float i1, const uint32_t (&a)[4], uint32_t bar, bool lane0) {
    constexpr int b = 32 * C + 16 * H;
#pragma unroll
    for (int i = 0; i < 16; i++) asm volatile("" : "+f"(o[b + i])::"memory");
    float r[8];
#pragma unroll
    for (int i = 0; i < 8; i++) {
        const float f = (i & 1) ? i1 : i0;
        r[i] = __uint_as_float(pack_bf16(o[b + 2 * i] * f, o[b + 2 * i + 1] * f));
        if (i == 3) {
            asm volatile("" : "+f"(r[0]), "+f"(r[1]), "+f"(r[2]), "+f"(r[3])::"memory");
            sched_point();
        }
    }
    stsm_x4<C * 8192>(a[2 * H], r[0], r[1], r[2], r[3]);
    stsm_x4<C * 8192>(a[2 * H + 1], r[4], r[5], r[6], r[7]);
    if (H == 1) {
        __syncwarp();
        mbar_arrive_if(lane0, bar + 8 * C);
    }
    sched_point();
}
template <int C, int K0, int K1>
__device__ __forceinline__ void issue_pv_tail(float (&o)[128], const uint32_t (&p)[16], const uint32_t (&q)[32], const uint64_t (&v)[3]) {
    wg_fence();
#pragma unroll
    for (int k = K0; k < K1; k++) {
        const uint64_t d = v[k >> 2] + C * 512 + (k & 3) * 128;
        if (k < 8) wgmma_rs_n64_tb<C>(o, q[4 * k], q[4 * k + 1], q[4 * k + 2], q[4 * k + 3], d);
        else wgmma_rs_n64_tb<C>(o, p[4 * k - 32], p[4 * k - 31], p[4 * k - 30], p[4 * k - 29], d);
    }
    wg_commit();
}


__global__ void __launch_bounds__(384, 1)
gqa_kernel(const uint8_t* __restrict__ qptr, const __grid_constant__ Maps maps, const __grid_constant__ Sched sched) {
    extern __shared__ __align__(1024) uint8_t smem[];
    const uint32_t slots = (uint32_t)__cvta_generic_to_shared(smem);
    const uint32_t bar_full = slots + kSlots * kSlotBytes + kBarFull;
    const uint32_t bar_empty = bar_full + kBarEmpty, bar_qlo = bar_full + kBarQLo, bar_qhi = bar_full + kBarQHi;
    const uint32_t bar_staged = bar_full + kBarStaged, bar_stored = bar_full + kBarStored;

    const int triple = blockIdx.x / 3, sub = blockIdx.x - triple * 3;
    const int grp = triple / 11, pos = triple - grp * 11;
    const int var = pos == kShortPos;
    const int ntiles = 3 - var;
    const int pair_first = var ? 120 + grp : grp * 10 + pos - (pos > kShortPos);
    const int pair_step = var ? 4 : 40;
    const int q_row = pair_first * kRowsPerPair + sub * 128, kv_row = pair_first * kKeys;
    const uint32_t delay = var ? kShortDelay : 0;
    asm volatile("{ .reg .pred p; setp.ne.u32 p, %1, 0; @p prefetch.global.L2 [%0]; }"
                 ::"l"(qptr + (size_t)(q_row + (threadIdx.x & 63)) * 512 + (threadIdx.x >> 6) * 128),
                   "r"((uint32_t)(threadIdx.x < kEarlyLines && !delay)) : "memory");
    const int wg = __shfl_sync(0xffffffffu, threadIdx.x >> 7, 0);
    const int warp = __shfl_sync(0xffffffffu, threadIdx.x >> 5, 0);

    uint64_t pol;
    asm volatile("createpolicy.fractional.L2::evict_first.b64 %0, 1.0;" : "=l"(pol));
    auto issue_load = [&](const CUtensorMap* m, uint32_t dst, uint32_t bar, uint32_t bytes, int row, int chunk) INLINE {
        mbar_expect_tx(bar, bytes);
        tma_load(dst, m, row, chunk, bar, pol);
    };
    auto first_loads = [&](int from, int to) INLINE {
        if (from <= 0 && 0 < to) issue_load(&maps.q, slots, bar_qlo, kSlotBytes / 2, q_row, 0);
        if (from <= 1 && 1 < to) issue_load(&maps.q, slots + kSlotBytes, bar_qhi, kSlotBytes / 2, q_row, 2);
        if (from <= 2 && 2 < to) issue_load(&maps.k, slots + 2 * kSlotBytes, bar_full + 16, kSlotBytes, kv_row, 0);
        if (from <= 3 && 3 < to) issue_load(&maps.k, slots + 3 * kSlotBytes, bar_full + 24, kSlotBytes, kv_row + 64, 0);
        if (from <= 4 && 4 < to) issue_load(&maps.q, slots + kSlotBytes / 2, bar_qlo + 8, kSlotBytes / 2, q_row + 64, 0);
        if (from <= 5 && 5 < to) issue_load(&maps.q, slots + 3 * kSlotBytes / 2, bar_qhi + 8, kSlotBytes / 2, q_row + 64, 2);
        if (from <= 6 && 6 < to) issue_load(&maps.v, slots + 4 * kSlotBytes, bar_full + 32, kSlotBytes, kv_row, 0);
        if (from <= 7 && 7 < to) issue_load(&maps.k, slots + 5 * kSlotBytes, bar_full + 40, kSlotBytes, kv_row + 128, 0);
        if (from <= 8 && 8 < to) issue_load(&maps.v, slots + 6 * kSlotBytes, bar_full + 48, kSlotBytes, kv_row + 64, 0);
    };

    uint32_t t_entry = 0;
    if (warp == 8) {
        if (elect_one()) {
            prefetch_map(&maps.q);
            prefetch_map(&maps.k);
            mbar_init(bar_qlo, 1);
            mbar_init(bar_qhi, 1);
            mbar_init(bar_full + 16, 1);
            asm volatile("fence.mbarrier_init.release.cluster;" ::: "memory");
            if (!delay) first_loads(0, 3);
        }
        t_entry = clock32();
    } else if (warp == 9) {
        if (elect_one()) {
            if (slots & 1023) __trap();
            prefetch_map(&maps.v);
            mbar_init(bar_qlo + 8, 1);
            mbar_init(bar_qhi + 8, 1);
#pragma unroll
            for (int i = 0; i < kSlots; i++) {
                if (i != 2) mbar_init(bar_full + 8 * i, 1);
                mbar_init(bar_empty + 8 * i, 8);
            }
#pragma unroll
            for (int i = 0; i < 8; i++) mbar_init(bar_staged + 8 * i, 4);
            mbar_init(bar_stored, 1);
            mbar_init(bar_stored + 8, 1);
            asm volatile("fence.mbarrier_init.release.cluster;" ::: "memory");
        }
    }
    __syncthreads();

    if (wg == 2) {
        asm volatile("setmaxnreg.dec.sync.aligned.u32 24;");
        if (warp == 9) {
            if (elect_one()) {
                prefetch_map(&maps.o);
                prefetch_map(&maps.o_piece);
            }
            int row = q_row;
            for (int t = 0; t < ntiles - 1; t++, row += pair_step * kRowsPerPair) {
                const uint32_t e = sched.cons[var].qo[t + 1];
#pragma unroll 1
                for (int w = 0; w < 2; w++) {
                    const uint32_t src = slots + ((e >> (8 + 4 * w)) & 7) * kSlotBytes;
                    const uint32_t ns = w ? kStoreNs1 : kStoreNs0;
#pragma unroll
                    for (int c = 0; c < 4; c++) {
                        mbar_wait_relaxed(bar_staged + 32 * w + 8 * c, t & 1);
                        asm volatile("fence.proxy.async.shared::cta;" ::: "memory");
#pragma unroll 1
                        for (int r = 0; r < 64; r += kStoreRows) {
                            if (elect_one()) tma_store(&maps.o_piece, src + c * 8192 + r * 128, row + w * 64 + r, c);
                            if (!(c == 3 && r + kStoreRows == 64)) __nanosleep(ns);
                        }
                    }
                    if (elect_one()) {
                        asm volatile("cp.async.bulk.commit_group;" ::: "memory");
                        asm volatile("cp.async.bulk.wait_group.read 0;" ::: "memory");
                        mbar_arrive(bar_stored + 8 * w);
                    }
                }
            }
            const uint32_t e = sched.cons[var].qo[ntiles];
#pragma unroll
            for (int i = 0; i < 8; i++) {
                uint32_t src = slots + ((e >> (8 + 4 * (i & 1))) & 7) * kSlotBytes + (i >> 1) * 8192;
                int r = row + (i & 1) * 64, c = i >> 1;
                const CUtensorMap* m = &maps.o;
                asm volatile("" : "+r"(src), "+r"(r), "+r"(c), "+l"(m));
                mbar_wait_relaxed(bar_staged + 32 * (i & 1) + 8 * (i >> 1), (ntiles - 1) & 1);
                asm volatile("fence.proxy.async.shared::cta;" ::: "memory");
                if (elect_one()) tma_store(m, src, r, c);
            }
            if (elect_one()) {
                asm volatile("cp.async.bulk.commit_group;" ::: "memory");
                asm volatile("cp.async.bulk.wait_group.read 0;" ::: "memory");
            }
        } else if (warp == 8) {
            if (delay) {
                while (clock32() - t_entry < delay) __nanosleep(32);
                if (elect_one()) first_loads(0, 3);
            }
            const uint32_t t0 = t_entry + delay + kPace0;
            int cum = 2 * kPace;
#pragma unroll
            for (int i = 3; i < 9; i++) {
                while ((int)(clock32() - t0) < cum) {}
                if (elect_one()) first_loads(i, i + 1);
                cum += (i == 4 || i == 5 ? 3 : 2) * kPace;
            }
            const uint8_t* pf = qptr + (size_t)q_row * 512;
            uint32_t base, bars;
            asm volatile("mov.u32 %0, %1;" : "=r"(base) : "r"(slots));
            asm volatile("mov.u32 %0, %1;" : "=r"(bars) : "r"(bar_full));
#pragma unroll 1
            for (int i = kSlots; i < 20 * ntiles - 2; i++) {
                const uint4 e = sched.load[var][i];
                const uint32_t moff = e.w & 0x180;
                const CUtensorMap* m = reinterpret_cast<const CUtensorMap*>(reinterpret_cast<const uint8_t*>(&maps) + moff);
                uint32_t dst = base + (e.y & 0x3c000), bar = bars + (e.y & 0xff), bytes = moff ? kSlotBytes : kSlotBytes / 2;
                int row = (moff ? kv_row : q_row) + e.z, chunk = e.w & 3;
                asm volatile("" : "+r"(dst), "+r"(bar), "+r"(bytes), "+r"(row), "+r"(chunk), "+l"(m));
                mbar_wait_relaxed(bars + (e.x & 0xff), e.x >> 31);
                if (elect_one()) issue_load(m, dst, bar, bytes, row, chunk);
                if ((e.x & 0xff00) && elect_one())
                    asm volatile("cp.async.bulk.prefetch.L2.global [%0], %1;"
                                 ::"l"(pf + ((e.w >> 12) << 10)), "r"((e.x & 0xff00) << 2) : "memory");
            }
        }
    } else {
        asm volatile("setmaxnreg.inc.sync.aligned.u32 240;");
        const bool lane0 = (threadIdx.x & 31) == 0;
        const uint64_t kmaj = sched.cons[var].desc_hi + ((slots >> 4) | (1u << 16));
        const uint64_t nmaj = sched.cons[var].desc_hi + ((slots >> 4) | (512u << 16));
        const int my_turn = 1 + wg, other_turn = 2 - wg;
        const uint32_t staged = bar_staged + 32 * wg;
        float o[128], s[32];
        uint32_t p[16], q[32];
        float c0, c1, l0 = 0.f, l1 = 0.f, a0 = 1.f, a1 = 1.f, r0, r1;
        int t0, t1;

        uint64_t kv = sched.cons[var].kv[0];
        uint32_t qo = sched.cons[var].qo[0];
        uint64_t q_desc = kmaj + (qo & 7) * 2048 + wg * 1024;
        uint32_t addr[4];
        bool k_ready;
        auto probe_next = [&]() INLINE { k_ready = mbar_test(bar_full + 8 * ((uint32_t)kv & 7), ((uint32_t)kv >> 3) & 1); };

        {
            float s0[32];
            auto half_rs = [&](float (&d)[32], uint64_t k_desc) INLINE {
                wg_fence();
                wgmma_rs_n64<0>(d, q[0], q[1], q[2], q[3], k_desc);
#pragma unroll
                for (int k = 1; k < 8; k++)
                    wgmma_rs_n64<1>(d, q[4 * k], q[4 * k + 1], q[4 * k + 2], q[4 * k + 3], k_desc + (k >> 2) * 512 + (k & 3) * 2);
            };
            auto half_ss = [&](float (&d)[32], uint64_t k_desc) INLINE {
#pragma unroll
                for (int k = 0; k < 8; k++)
                    wgmma_ss_n64<1>(d, q_desc + (k >> 2) * 512 + (k & 3) * 2, k_desc + 1024 + (k >> 2) * 512 + (k & 3) * 2);
                wg_commit();
            };
            mbar_wait(bar_qlo + 8 * wg, 0);
            tile_addr(addr, slots + wg * (kSlotBytes / 2));
            load_q(q, addr);
            mbar_arrive_if(lane0, bar_empty + after_load_q(q, qo >> 28));
            mbar_wait(bar_full + 16, 0);
            half_rs(s0, kmaj + 2 * 2048);
            mbar_wait(bar_full + 24, 0);
            half_rs(s, kmaj + 3 * 2048);
            mbar_wait(bar_qhi + 8 * wg, 0);
            wg_fence();
            half_ss(s0, kmaj + 2 * 2048);
            half_ss(s, kmaj + 3 * 2048);
            if (wg == 1) bar_arrive(1, 256);
            wg_wait<1>();
            fence_regs(s0);
            mbar_arrive_if(lane0, bar_empty + 16);
            set_max(s0, c0, c1, t0, t1);
            asm volatile("" : "+f"(c0), "+f"(c1)::"memory");
            sched_point();
            wg_wait<0>();
            fence_regs(s);
            mbar_arrive_if(lane0, bar_empty + 24);
            exp_groups<0, 8>(s0, c0, c1, [&]() INLINE { sum_groups<3>(s0, r0, r1); });
            pack_and_sum(s0, p, l0, l1, r0, r1);
            fence_regs(p);
            asm volatile("" : "+f"(l0), "+f"(l1)::"memory");
            sched_point();
        }

        auto step = [&](int j, int t, auto kind) INLINE {
            constexpr int KIND = decltype(kind)::value;
            constexpr int NP = KIND == 0 ? kExpBeforePv : KIND == 3 ? kExpBeforePvLast : 0;
            const uint32_t e = (uint32_t)kv, ks = e & 7, vs = (e >> 4) & 7, os = (qo >> (8 + 4 * wg)) & 7;
            if (KIND == 1) kv = sched.cons[var].kv[t + 1];
            else kv >>= 8;
            if constexpr (KIND != 4) {
                if (!k_ready) {
                    mbar_wait(bar_full + 8 * ks, (e >> 3) & 1);
                    if (KIND == 1) mbar_wait(bar_qhi + 8 * wg, (t + 1) & 1);
                }
                bar_sync(my_turn, 256);
                wg_fence();
                issue_qk<0>(s, q, q_desc + (e & (qo >> 28)), kmaj + ks * 2048, [&](auto k) INLINE {
                    if constexpr (KIND == 2) {
                        constexpr int K = decltype(k)::value;
                        constexpr int from = kEpi1 + K * (kEpi2 - kEpi1) / 8, to = kEpi1 + (K + 1) * (kEpi2 - kEpi1) / 8;
                        if constexpr (from < to && to <= kEpi2) {
                            stage_groups<from, to>(o, a0, a1, addr, staged, lane0);
                            wg_fence();
                        }
                    }
                });
                bar_arrive(other_turn, 256);
            }
            if constexpr (KIND == 2) stage_groups<kEpi2, kEpi3>(o, a0, a1, addr, staged, lane0);
            const bool v_ready = mbar_test(bar_full + 8 * vs, (e >> 7) & 1);
            uint32_t qo_next = 0;
            if (KIND == 3) {
                qo_next = sched.cons[var].qo[t + 1];
                tile_addr(addr, slots + ((qo_next >> 4) & 7) * kSlotBytes + wg * (kSlotBytes / 2));
            }
            if (KIND == 1) tile_addr(addr, slots + os * kSlotBytes);
            if (KIND != 4) {
                sched_point();
                wg_wait<0>();
                fence_regs(s);
                mbar_arrive_if(lane0, bar_empty + 8 * ks);
            }
            if (KIND == 3) {
                mbar_arrive_if(lane0, bar_empty + 8 * (qo & 7));
                fence_regs(q);
                qo = qo_next;
                q_desc = kmaj + (qo & 7) * 2048 + wg * 1024;
            }
            sched_point();
            bool rescale = false;
            auto check = [&]() INLINE {
                rescale = __any_sync(0xffffffffu, over_limit(s, t0, t1));
                if (rescale) raise_max(s, c0, c1, t0, t1, a0, a1);
            };
            if (KIND == 0 || KIND == 3) check();
            if (KIND == 1) set_max(s, c0, c1, t0, t1);
            if constexpr (KIND == 2) stage_groups<kEpi3, 17>(o, a0, a1, addr, staged, lane0);
            exp_groups<0, NP>(s, c0, c1, []() INLINE {});
            if (!v_ready) mbar_wait(bar_full + 8 * vs, (e >> 7) & 1);
            bar_sync(my_turn, 256);
            fence_regs(o); fence_regs(p);
            wg_fence();
            issue_pv(o, p, nmaj + vs * 2048, KIND == 1 || j > 1);
            bar_arrive(other_turn, 256);
            if (KIND == 2 || KIND == 4) check();
            if (KIND == 3) {
                mbar_wait(bar_qlo + 8 * wg, (t + 1) & 1);
                load_q(q, addr);
            }
            exp_groups<NP, 8>(s, c0, c1, [&]() INLINE {
                if (KIND != 3) sum_groups<3>(s, r0, r1);
                if (KIND == 1) {
                    a0 = l0;
                    a1 = l1;
                    inv_row_sum(a0, a1);
                    l0 = 0.f;
                    l1 = 0.f;
                }
            });
            probe_next();
            if (KIND == 3) {
                k_ready = mbar_test(bar_qhi + 8 * wg, (t + 1) & 1) && k_ready;
                sum_groups<3>(s, r0, r1);
                sched_point();
                mbar_arrive_if(lane0, bar_empty + 8 * ((qo >> 4) & 7) + after_load_q(q, qo >> 28));
            }
            sched_point();
            wg_wait<0>();
            fence_regs(o); fence_regs(p);
            mbar_arrive_if(lane0, bar_empty + 8 * vs);
            if (rescale) {
                l0 *= a0;
                l1 *= a1;
                rescale_o(o, a0, a1);
            }
            pack_and_sum(s, p, l0, l1, r0, r1);
            if (KIND == 1) {
                mbar_wait(bar_empty + 8 * os, (qo >> (11 + 4 * wg)) & 1);
                stage_groups<0, kEpi1>(o, a0, a1, addr, staged, lane0);
            }
            fence_regs(p);
        };
        step(1, 0, Idx<4>());
        for (int t = 0;; t++) {
#pragma unroll 1
            for (int j = 2; j < 7 - 2 * (t == ntiles - 1); j++) step(j, t, Idx<0>());
            if (t == ntiles - 1) break;
            step(7, t, Idx<3>());
            step(0, t, Idx<1>());
            step(1 + (qo >> 28), t, Idx<2>());
        }

        const uint32_t qh_slot = qo & 7;
        qo = sched.cons[var].qo[ntiles];
        const uint32_t e = (uint32_t)kv, os = (qo >> (8 + 4 * wg)) & 7;
        float f0 = 1.f, f1 = 1.f;
        auto end_step = [&](auto ji) INLINE {
            constexpr int J = decltype(ji)::value;
            constexpr int k0 = J == 0 ? 0 : J == 1 ? kFill5 : kFill6, k1 = J == 0 ? kFill5 : J == 1 ? kFill6 : 4;
            const uint32_t ks = (e >> (8 * J)) & 7;
            if (!k_ready) mbar_wait(bar_full + 8 * ks, (e >> (8 * J + 3)) & 1);
            bar_sync(my_turn, 256);
            wg_fence();
            wgmma_ss_n64_rt(s, q_desc, kmaj + ks * 2048 + 1024, qo >> 28);
            issue_qk<1>(s, q, q_desc, kmaj + ks * 2048, [](auto) INLINE {});
            if (J == 0) mbar_wait(bar_full + 8 * ((e >> 4) & 7), (e >> 7) & 1);
            fence_regs(o);
            wg_fence();
#pragma unroll
            for (int k = k0; k < k1; k++)
                wgmma_rs_n256_tb(o, p[4 * k], p[4 * k + 1], p[4 * k + 2], p[4 * k + 3], nmaj + ((e >> 4) & 7) * 2048 + k * 128, 1);
            wg_commit();
            bar_arrive(other_turn, 256);
            if (J == 0) {
                tile_addr(addr, slots + (qo & 7) * kSlotBytes + wg * (kSlotBytes / 2));
                mbar_wait(bar_empty + 8 * (qo & 7), (qo >> 3) & 1);
            }
            if (J < 2) k_ready = mbar_test(bar_full + 8 * ((e >> (8 * J + 8)) & 7), (e >> (8 * J + 11)) & 1);
            else k_ready = mbar_test(bar_full + 8 * ((e >> 12) & 7), (e >> 15) & 1) & mbar_test(bar_full + 8 * ((e >> 20) & 7), (e >> 23) & 1);
            sched_point();
            wg_wait<1>();
            fence_regs(s);
            mbar_arrive_if(lane0, bar_empty + 8 * ks);
            if (J == 2) {
                mbar_arrive_if(lane0, bar_empty + 8 * qh_slot);
                fence_regs(q);
                load_q(q, addr);
            }
            if (__any_sync(0xffffffffu, over_limit(s, t0, t1))) {
                raise_max(s, c0, c1, t0, t1, a0, a1);
                l0 *= a0;
                l1 *= a1;
                f0 *= a0;
                f1 *= a1;
                if (J == 1) {
#pragma unroll
                    for (int h = 0; h < 4; h++) {
                        uint32_t x[4];
                        ldsm_x4(addr[h], x[0], x[1], x[2], x[3]);
                        rescale_p(x, a0, a1);
                        stsm_x4<0>(addr[h], __uint_as_float(x[0]), __uint_as_float(x[1]), __uint_as_float(x[2]), __uint_as_float(x[3]));
                    }
                }
                if (J == 2) rescale_p(q, a0, a1);
            }
            if (J == 2) return;
            exp_pipelined(s, c0, c1, [&](auto hi) INLINE {
                constexpr int h = decltype(hi)::value;
                l0 += (s[8 * h] + s[8 * h + 1]) + (s[8 * h + 4] + s[8 * h + 5]);
                l1 += (s[8 * h + 2] + s[8 * h + 3]) + (s[8 * h + 6] + s[8 * h + 7]);
#pragma unroll
                for (int i = 0; i < 4; i++) s[8 * h + i] = __uint_as_float(pack_bf16(s[8 * h + 2 * i], s[8 * h + 2 * i + 1]));
                stsm_x4<J * 8192>(addr[h], s[8 * h], s[8 * h + 1], s[8 * h + 2], s[8 * h + 3]);
                asm volatile("" : "+f"(l0), "+f"(l1)::"memory");
            });
        };
        end_step(Idx<0>());
        end_step(Idx<1>());
        end_step(Idx<2>());
        auto scale_chunk = [&](auto ci) INLINE {
            constexpr int C = decltype(ci)::value;
#pragma unroll
            for (int i = 0; i < 32; i++) {
                o[32 * C + i] *= (i & 2) ? f1 : f0;
                asm volatile("" : "+f"(o[32 * C + i])::"memory");
                if (i % 8 == 7) sched_point();
            }
        };
        exp_pipelined(s, c0, c1, [&](auto hi) INLINE {
            constexpr int h = decltype(hi)::value;
            if (h == 0) {
                wg_wait<0>();
                fence_regs(o); fence_regs(p);
            }
            l0 += (s[8 * h] + s[8 * h + 1]) + (s[8 * h + 4] + s[8 * h + 5]);
            l1 += (s[8 * h + 2] + s[8 * h + 3]) + (s[8 * h + 6] + s[8 * h + 7]);
#pragma unroll
            for (int i = 4 * h; i < 4 * h + 4; i++) {
                p[i] = pack_bf16(s[2 * i], s[2 * i + 1]);
                asm volatile("" : "+r"(p[i])::"memory");
            }
#pragma unroll
            for (int i = (h < 2 ? 12 * h : 16 + 4 * h); i < (h < 2 ? 12 * h + 12 : 20 + 4 * h); i++) {
                o[i] *= (i & 2) ? f1 : f0;
                asm volatile("" : "+f"(o[i])::"memory");
            }
            asm volatile("" : "+f"(l0), "+f"(l1)::"memory");
        });
        const uint64_t v_desc[3] = {nmaj + ((e >> 12) & 7) * 2048, nmaj + ((e >> 20) & 7) * 2048, nmaj + ((e >> 28) & 7) * 2048};
        if (!k_ready) {
            mbar_wait(bar_full + 8 * ((e >> 12) & 7), (e >> 15) & 1);
            mbar_wait(bar_full + 8 * ((e >> 20) & 7), (e >> 23) & 1);
        }
        auto finish_chunk = [&](auto ci) INLINE {
            constexpr int C = decltype(ci)::value;
            bar_sync(my_turn, 256);
            fence_regs(p); fence_regs(q);
            if (C == 0) {
                issue_pv_tail<C, 0, 8>(o, p, q, v_desc);
                mbar_wait(bar_full + 8 * ((e >> 28) & 7), e >> 31);
                issue_pv_tail<C, 8, 12>(o, p, q, v_desc);
            } else {
                issue_pv_tail<C, 0, 12>(o, p, q, v_desc);
            }
            if (C < 3 || wg == 0) bar_arrive(other_turn, 256);
            if (C == 0) {
                a0 = l0;
                a1 = l1;
                inv_row_sum(a0, a1);
                tile_addr(addr, slots + os * kSlotBytes);
                mbar_wait(bar_empty + 8 * os, (qo >> (11 + 4 * wg)) & 1);
            }
            if constexpr (C > 0 && C < 3) scale_chunk(Idx<C + 1>());
            wg_wait<0>();
            fence_regs(p); fence_regs(q);
            stage_half<C, 0>(o, a0, a1, addr, staged, lane0);
            stage_half<C, 1>(o, a0, a1, addr, staged, lane0);
            if constexpr (C == 0) scale_chunk(Idx<1>());
        };
        finish_chunk(Idx<0>());
        finish_chunk(Idx<1>());
        finish_chunk(Idx<2>());
        finish_chunk(Idx<3>());
    }
}


typedef CUresult (*EncodeTiledFn)(CUtensorMap*, CUtensorMapDataType, cuuint32_t, void*, const cuuint64_t*,
                                  const cuuint64_t*, const cuuint32_t*, const cuuint32_t*, CUtensorMapInterleave,
                                  CUtensorMapSwizzle, CUtensorMapL2promotion, CUtensorMapFloatOOBfill);

void make_map(EncodeTiledFn enc, CUtensorMap* m, void* ptr, uint64_t rows, uint32_t box_rows, uint32_t box_chunks) {
    cuuint64_t dims[3] = {64, rows, 4};
    cuuint64_t strides[2] = {512, 128};
    cuuint32_t box[3] = {64, box_rows, box_chunks};
    cuuint32_t es[3] = {1, 1, 1};
    enc(m, CU_TENSOR_MAP_DATA_TYPE_BFLOAT16, 3, ptr, dims, strides, box, es, CU_TENSOR_MAP_INTERLEAVE_NONE,
        CU_TENSOR_MAP_SWIZZLE_128B, CU_TENSOR_MAP_L2_PROMOTION_L2_128B, CU_TENSOR_MAP_FLOAT_OOB_FILL_NONE);
}

void build_sched(Sched* sc) {
    enum { Q = 0, K = 1, V = 2 };
    for (int var = 0; var < 2; var++) {
        const int nt = 3 - var, pair_step = var ? 4 : 40;
        struct Item { int kind, tile, j, wg; };
        Item loads[kMaxLoads], frees[kMaxLoads];
        int nl = 0, nf = 0;
        loads[nl++] = {Q, 0, 0, 0};
        loads[nl++] = {Q, 0, 1, 0};
        loads[nl++] = {K, 0, 0, 0};
        for (int t = 0; t < nt; t++) {
            for (int pos = 0; pos < 16; pos++) {
                for (int k = 0; k < 4 && t + 1 < nt; k++)
                    if (kQPos[t][k] == pos) loads[nl++] = {Q, t + 1, 1 - (k >> 1), k & 1};
                if (t + 1 == nt && pos == 11) loads[nl++] = {K, t, 7, 0};
                else if (t + 1 == nt && pos == 12) loads[nl++] = {V, t, 5, 0};
                else if (pos & 1) loads[nl++] = {V, t, pos >> 1, 0};
                else if (pos < 14) loads[nl++] = {K, t, pos / 2 + 1, 0};
                else if (t + 1 < nt) loads[nl++] = {K, t + 1, 0, 0};
            }
        }
        frees[nf++] = {Q, 0, 0, 0};
        for (int t = 0; t < nt; t++) {
            int pos = 0;
            auto push = [&](Item it) {
                if (t && pos == kStored0Pos) frees[nf++] = {Q, t, 0, 0};
                if (t && pos == kStored1Pos) frees[nf++] = {V, t - 1, 7, 0};
                frees[nf++] = it;
                pos++;
            };
            push({K, t, 0, 0});
            for (int j = 1; j < 8; j++) {
                push({K, t, j, 0});
                if (j == 7) push({Q, t, 1, 0});
                if (t + 1 < nt || j < 4) push({V, t, j - 1, 0});
            }
        }
        int slot_of[3][3][8], use_of[3][3][8], fill_of[3][3][8];
        uint32_t wait_of[3][2];
        int uses[kSlots] = {0}, fills[kSlots] = {0}, pf_pos = 0, na = 0;
        for (int i = 0; i < nl; i++) {
            const Item l = loads[i];
            int slot = na;
            uint4 e = {0, 0, 0, 0};
            if (l.wg) {
                slot = slot_of[Q][l.tile][l.j];
                e.x = wait_of[l.tile][l.j];
            } else {
                if (na >= kSlots) {
                    const Item f = frees[na - kSlots];
                    slot = slot_of[f.kind][f.tile][f.j];
                    if (f.kind == Q && f.j == 0 && f.tile) e.x = kBarStored | (uint32_t)((f.tile - 1) & 1) << 31;
                    else if (f.kind == V && f.j == 7) e.x = (kBarStored + 8) | (uint32_t)(f.tile & 1) << 31;
                    else e.x = (kBarEmpty + 8 * slot) | (uint32_t)(use_of[f.kind][f.tile][f.j] & 1) << 31;
                }
                na++;
                slot_of[l.kind][l.tile][l.j] = slot;
                use_of[l.kind][l.tile][l.j] = uses[slot]++;
                if (l.kind == Q) wait_of[l.tile][l.j] = e.x;
                else fill_of[l.kind][l.tile][l.j] = fills[slot]++;
            }
            e.y = (l.kind == Q ? (l.j ? kBarQHi : kBarQLo) + 8 * l.wg : kBarFull + 8 * slot) | (slot * kSlotBytes + l.wg * kSlotBytes / 2);
            e.z = l.tile * pair_step * (l.kind == Q ? kRowsPerPair : kKeys) + (l.kind == Q ? l.wg : l.j) * 64;
            e.w = l.kind * sizeof(CUtensorMap) | (l.kind == Q ? 2 * l.j : 0);
            int kb = 0;
            for (int w = 0; w < 2; w++)
                if (i >= kPf[w][0] && i < kPf[w][1]) kb = kPf[w][2];
            if (l.kind == Q && l.j == 0 && l.wg == 1 && pf_pos < 64 * l.tile) pf_pos = 64 * l.tile;
            const int pt = 1 + pf_pos / 64, n = kb < 64 - pf_pos % 64 ? kb : 64 - pf_pos % 64;
            if (kb && pt < nt) {
                e.x |= n << 8;
                e.w |= (pt * pair_step * kRowsPerPair / 2 + pf_pos % 64) << 12;
                pf_pos += n;
            }
            sc->load[var][i] = e;
        }
        auto full = [&](int kind, int t, int j) { return (uint32_t)(slot_of[kind][t][j] | (fill_of[kind][t][j] & 1) << 3); };
        auto empty = [&](Item f) { return (uint32_t)(slot_of[f.kind][f.tile][f.j] | (use_of[f.kind][f.tile][f.j] & 1) << 3); };
        ConsumerSched& c = sc->cons[var];
        c.desc_hi = (uint64_t)(0x40000000u | 64u) << 32;
        for (int t = 0; t <= nt; t++) {
            c.qo[t] = t < nt ? slot_of[Q][t][1] | slot_of[Q][t][0] << 4 : 0;
            if (t > 0 && t < nt) c.qo[t] |= empty({Q, t, 0, 0}) << 8 | empty({V, t - 1, 7, 0}) << 12;
            if (t == nt) c.qo[t] = empty({V, t - 1, 3, 0}) | empty({K, t - 1, 7, 0}) << 8 | empty({Q, t - 1, 1, 0}) << 12;
        }
        for (int t = 0; t < nt; t++) {
            c.kv[t] = 0;
            for (int j = 0; j < 8; j++) {
                const uint32_t k = j < 7 ? full(K, t, j + 1) : t + 1 < nt ? full(K, t + 1, 0) : 0;
                c.kv[t] |= (uint64_t)(k | full(V, t, j) << 4) << (8 * j);
            }
        }
    }
}

}

extern "C" void kernel_launch(void* const* d_in, const int* in_sizes, int n_in, void* d_out, int out_size) {
    (void)in_sizes; (void)n_in; (void)out_size;
    static EncodeTiledFn enc = nullptr;
    static Sched sched;
    if (!enc) {
        void* fn = nullptr;
        cudaDriverEntryPointQueryResult qr;
        cudaGetDriverEntryPoint("cuTensorMapEncodeTiled", &fn, cudaEnableDefault, &qr);
        enc = (EncodeTiledFn)fn;
        build_sched(&sched);
        cudaFuncSetAttribute(gqa_kernel, cudaFuncAttributeMaxDynamicSharedMemorySize, kSmemBytes);
    }
    Maps maps;
    make_map(enc, &maps.q, d_in[0], (uint64_t)kPairs * kRowsPerPair, 64, 2);
    make_map(enc, &maps.k, d_in[1], (uint64_t)kPairs * kKeys, 64, 4);
    make_map(enc, &maps.v, d_in[2], (uint64_t)kPairs * kKeys, 64, 4);
    make_map(enc, &maps.o, d_out, (uint64_t)kPairs * kRowsPerPair, 64, 1);
    make_map(enc, &maps.o_piece, d_out, (uint64_t)kPairs * kRowsPerPair, kStoreRows, 1);
    gqa_kernel<<<kGrid, 384, kSmemBytes, cudaStreamPerThread>>>((const uint8_t*)d_in[0], maps, sched);
}
```
